```python
import torch

def _softmax(x, axis=-1):
    return torch.softmax(x, dim=axis)
def _gelu(x):
    return torch.nn.functional.gelu(x, approximate="tanh")
def _silu(x):
    return torch.nn.functional.silu(x)
def _sigmoid(x):
    return torch.sigmoid(x)
def _layernorm(x, axis=-1, eps=1e-5):
    m = x.mean(dim=axis, keepdim=True)
    v = x.var(dim=axis, keepdim=True, unbiased=False)
    return (x - m) / torch.sqrt(v + eps)
def _scatter_add(tgt, idx, src, axis=0):
    return tgt.clone().index_add_(axis, idx, src)
def _segment_sum(src, seg, n):
    out = torch.zeros((n,) + src.shape[1:], dtype=src.dtype)
    return out.index_add_(0, seg, src)
def _pad(x, pw):
    flat = tuple(v for pair in reversed(pw) for v in pair)
    return torch.nn.functional.pad(x, flat)

kernel_name = 'sequential_preLN__sliding_block_cached__dense_activation_relu__decode'

def setup_inputs():

    _w = (lambda a: (lambda t: t.to(torch.bfloat16) if t.is_floating_point() else t)(torch.as_tensor(a)))
    def _A_setup():
        B, Sq, D = 8, 1, 576
        Hq, Hkv, Sk, Dh = 32, 16, 8192, 128
        assert Hq % Hkv == 0, (Hq, Hkv)
        return {
            "x": _w((lambda *s: torch.randn(*s, dtype=torch.bfloat16) * 0.05)(B, Sq, D)),
            "k_cache": _w((lambda *s: torch.randn(*s, dtype=torch.bfloat16) * 3.2)(B, Hkv, Sk, Dh)),
            "v_cache": _w((lambda *s: torch.randn(*s, dtype=torch.bfloat16) * 0.4)(B, Hkv, Sk, Dh)),
            "wq": _w((lambda *s: torch.randn(*s, dtype=torch.bfloat16) * 3.2)(D, Hq * Dh) * (D ** -0.5)),
            "wo": _w((lambda *s: torch.randn(*s, dtype=torch.bfloat16) * 0.4)(Hq * Dh, D) * ((Hq * Dh) ** -0.5)),
        }
    _A_in = _A_setup()

    def _B_setup():
        B, S, D, Dff = 8, 1, 576, 4608
        return {
            "x": _w((lambda *s: torch.randn(*s, dtype=torch.bfloat16) * 0.05)(B, S, D)),
            "w1": _w((lambda *s: torch.randn(*s, dtype=torch.bfloat16) * 0.05)(D, Dff)),
            "w2": _w((lambda *s: torch.randn(*s, dtype=torch.bfloat16) * 0.05)(Dff, D)),
        }
    _B_in = _B_setup()

    return {
        "A_x": _A_in["x"],
        "A_k_cache": _A_in["k_cache"],
        "A_v_cache": _A_in["v_cache"],
        "A_wq": _A_in["wq"],
        "A_wo": _A_in["wo"],
        "B_x": _B_in["x"],
        "B_w1": _B_in["w1"],
        "B_w2": _B_in["w2"],
    }

def reference(A_x, A_k_cache, A_v_cache, A_wq, A_wo, B_x, B_w1, B_w2):
    def _A_ref(x, k_cache, v_cache, wq, wo):
        B, Sq, D = x.shape
        Hq, Dh = 32, 128
        Hkv, Sk = k_cache.shape[1], k_cache.shape[2]
        W = min(4096, max(256, Sk // 4))
        rep = Hq // Hkv
        q = (lambda x, *d: x.permute(*d))((x @ wq).reshape(B, Sq, Hq, Dh), 0, 2, 1, 3)
        k = (lambda x, n, axis: torch.repeat_interleave(x, n, dim=axis))(k_cache[:, :, Sk - W:, :], rep, axis=1)
        v = (lambda x, n, axis: torch.repeat_interleave(x, n, dim=axis))(v_cache[:, :, Sk - W:, :], rep, axis=1)
        scores = torch.einsum("bhqd,bhkd->bhqk", q, k) * (Dh ** -0.5)
        p = _softmax(scores, axis=-1)
        o = torch.einsum("bhqk,bhkd->bhqd", p, v)
        return (lambda x, *d: x.permute(*d))(o, 0, 2, 1, 3).reshape(B, Sq, Hq * Dh) @ wo

    def _B_ref(x, w1, w2):
        h = torch.einsum("bsd,df->bsf", x, w1)
        zero = torch.zeros_like(h)
        h = torch.maximum(h, zero)
        return torch.einsum("bsf,fd->bsd", h, w2)

    x = A_x
    h = x + _A_ref(_layernorm(x, axis=-1), A_k_cache, A_v_cache, A_wq, A_wo)
    h2 = h + _B_ref(_layernorm(h, axis=-1), B_w1, B_w2)
    return h2
```

```cpp
#include <cuda_runtime.h>
#include <cuda_bf16.h>
#include <cuda.h>
#include <stdint.h>

namespace {

constexpr int NB = 8;
constexpr int DM = 576;
constexpr int HKV = 16;
constexpr int DH = 128;
constexpr int SK = 8192;
constexpr int WIN = 2048;
constexpr int DFF = 4608;
constexpr int NCTA = 128;

constexpr int SLOT = 16384;
constexpr int NS = 11;
constexpr int IT_WQ = 0;
constexpr int IT_K = 3;
constexpr int IT_V = 35;
constexpr int IT_WO = 67;
constexpr int IT_W1 = 70;
constexpr int IT_W2 = 73;
constexpr int N_ITEMS = 76;

constexpr int SM_RING = 0;
constexpr int SM_SC = NS * SLOT;
constexpr int SM_ACT = SM_SC + 8192;
constexpr int ACT_PITCH = 584;
constexpr int SM_RED = SM_ACT + NB * ACT_PITCH * 2;
constexpr int SM_QS = SM_RED + 32768;
constexpr int SM_STAT = SM_QS + 512;
constexpr int SM_BAR = SM_STAT + 128;
constexpr int SM_TOTAL = SM_BAR + 2 * NS * 8 + 64;
constexpr int OALL_PITCH = 264;
constexpr int H1_PITCH = 296;

struct Scratch {
    uint32_t q[HKV][NB][256];
    uint32_t o[HKV][NB][256];
    uint32_t ap[8][HKV][NB][72];
    uint32_t h[NB][DM];
    uint32_t h1[HKV][NB][288];
    uint32_t fp[8][HKV][NB][72];
};
__device__ __align__(128) Scratch g_scr;
__device__ uint32_t g_epoch;

#define DBG_T(i) do { } while (0)

#define PACE_PS_PER_KB 43008
#define PACE_LEAD 49152

__device__ __forceinline__ uint32_t smem_u32(const void* p) { return (uint32_t)__cvta_generic_to_shared(p); }
__device__ __forceinline__ unsigned long long gtime() {
    unsigned long long t; asm volatile("mov.u64 %0, %globaltimer;" : "=l"(t)); return t;
}
__device__ __forceinline__ void mbar_init(uint32_t bar, uint32_t cnt) {
    asm volatile("mbarrier.init.shared::cta.b64 [%0], %1;" ::"r"(bar), "r"(cnt) : "memory");
}
__device__ __forceinline__ void mbar_expect_tx(uint32_t bar, uint32_t bytes) {
    asm volatile("mbarrier.arrive.expect_tx.shared::cta.b64 _, [%0], %1;" ::"r"(bar), "r"(bytes) : "memory");
}
__device__ __forceinline__ void mbar_arrive(uint32_t bar) {
    asm volatile("mbarrier.arrive.shared::cta.b64 _, [%0];" ::"r"(bar) : "memory");
}
__device__ __forceinline__ bool mbar_try(uint32_t bar, uint32_t parity) {
    uint32_t ok;
    asm volatile("{\n.reg .pred p;\nmbarrier.try_wait.parity.shared::cta.b64 p, [%1], %2;\nselp.u32 %0, 1, 0, p;\n}"
                 : "=r"(ok) : "r"(bar), "r"(parity) : "memory");
    return ok != 0;
}
__device__ __forceinline__ void mbar_wait(uint32_t bar, uint32_t parity) {
    uint32_t spins = 0;
    while (!mbar_try(bar, parity)) {
        if (++spins > (1u << 22)) __trap();
    }
}
__device__ __forceinline__ void bulk_g2s(uint32_t dst, const void* src, uint32_t bytes, uint32_t bar) {
    asm volatile("cp.async.bulk.shared::cluster.global.mbarrier::complete_tx::bytes [%0], [%1], %2, [%3];"
                 ::"r"(dst), "l"(src), "r"(bytes), "r"(bar) : "memory");
}
__device__ __forceinline__ void tma_2d(uint32_t dst, const CUtensorMap* map, int x, int y, uint32_t bar) {
    asm volatile("cp.async.bulk.tensor.2d.shared::cluster.global.mbarrier::complete_tx::bytes [%0], [%1, {%3, %4}], [%2];"
                 ::"r"(dst), "l"(map), "r"(bar), "r"(x), "r"(y) : "memory");
}
__device__ __forceinline__ void cons_sync() { asm volatile("bar.sync 1, 256;" ::: "memory"); }

__device__ __forceinline__ uint4 lds128(uint32_t a) {
    uint4 v; asm volatile("ld.shared.v4.u32 {%0,%1,%2,%3}, [%4];" : "=r"(v.x), "=r"(v.y), "=r"(v.z), "=r"(v.w) : "r"(a)); return v;
}
__device__ __forceinline__ uint2 lds64(uint32_t a) {
    uint2 v; asm volatile("ld.shared.v2.u32 {%0,%1}, [%2];" : "=r"(v.x), "=r"(v.y) : "r"(a)); return v;
}
__device__ __forceinline__ void ldsm_x4(uint32_t& r0, uint32_t& r1, uint32_t& r2, uint32_t& r3, uint32_t a) {
    asm volatile("ldmatrix.sync.aligned.m8n8.x4.shared.b16 {%0,%1,%2,%3}, [%4];"
                 : "=r"(r0), "=r"(r1), "=r"(r2), "=r"(r3) : "r"(a));
}
__device__ __forceinline__ void ldsm_x2(uint32_t& r0, uint32_t& r1, uint32_t a) {
    asm volatile("ldmatrix.sync.aligned.m8n8.x2.shared.b16 {%0,%1}, [%2];" : "=r"(r0), "=r"(r1) : "r"(a));
}
__device__ __forceinline__ void ldsm_x4_t(uint32_t& r0, uint32_t& r1, uint32_t& r2, uint32_t& r3, uint32_t a) {
    asm volatile("ldmatrix.sync.aligned.m8n8.x4.trans.shared.b16 {%0,%1,%2,%3}, [%4];"
                 : "=r"(r0), "=r"(r1), "=r"(r2), "=r"(r3) : "r"(a));
}
__device__ __forceinline__ void mma16816(float (&c)[4], uint32_t a0, uint32_t a1, uint32_t a2, uint32_t a3, uint32_t b0, uint32_t b1) {
    asm volatile("mma.sync.aligned.m16n8k16.row.col.f32.bf16.bf16.f32 {%0,%1,%2,%3}, {%4,%5,%6,%7}, {%8,%9}, {%0,%1,%2,%3};"
                 : "+f"(c[0]), "+f"(c[1]), "+f"(c[2]), "+f"(c[3])
                 : "r"(a0), "r"(a1), "r"(a2), "r"(a3), "r"(b0), "r"(b1));
}
__device__ __forceinline__ uint4 ld_poll4(const uint32_t* p) {
    uint4 v;
    asm volatile("ld.relaxed.gpu.global.v4.u32 {%0,%1,%2,%3}, [%4];" : "=r"(v.x), "=r"(v.y), "=r"(v.z), "=r"(v.w) : "l"(p) : "memory");
    return v;
}
__device__ __forceinline__ void st_pub(uint32_t* p, uint32_t v) {
    asm volatile("st.relaxed.gpu.global.u32 [%0], %1;" ::"l"(p), "r"(v) : "memory");
}
__device__ __forceinline__ void st_pub4(uint32_t* p, uint4 v) {
    asm volatile("st.relaxed.gpu.global.v4.u32 [%0], {%1,%2,%3,%4};" ::"l"(p), "r"(v.x), "r"(v.y), "r"(v.z), "r"(v.w) : "memory");
}
__device__ __forceinline__ uint32_t bf16_bits(float f) {
    return (uint32_t)__bfloat16_as_ushort(__float2bfloat16_rn(f));
}
__device__ __forceinline__ float bf16r(float f) { return __uint_as_float(bf16_bits(f) << 16); }
__device__ __forceinline__ float bf_lo(uint32_t w) { return __uint_as_float(w << 16); }
__device__ __forceinline__ float bf_hi(uint32_t w) { return __uint_as_float(w & 0xffff0000u); }
__device__ __forceinline__ uint32_t pack_hi16(uint32_t lo_word, uint32_t hi_word) {
    return __byte_perm(lo_word, hi_word, 0x7632);
}
__device__ __forceinline__ uint4 poll_bf16x4(const uint32_t* p, uint32_t tag16) {
    uint32_t spins = 0;
    while (true) {
        uint4 v = ld_poll4(p);
        uint32_t bad = ((v.x ^ tag16) | (v.y ^ tag16) | (v.z ^ tag16) | (v.w ^ tag16)) & 0xffffu;
        if (bad == 0) return v;
        if (++spins > (1u << 22)) __trap();
    }
}
__device__ __forceinline__ uint4 poll_f32x4(const uint32_t* p, uint32_t tag2) {
    uint32_t spins = 0;
    while (true) {
        uint4 v = ld_poll4(p);
        uint32_t bad = ((v.x ^ tag2) | (v.y ^ tag2) | (v.z ^ tag2) | (v.w ^ tag2)) & 3u;
        if (bad == 0) return v;
        if (++spins > (1u << 22)) __trap();
    }
}
__device__ __forceinline__ float warp_sum(float v) {
#pragma unroll
    for (int o = 16; o > 0; o >>= 1) v += __shfl_xor_sync(0xffffffffu, v, o);
    return v;
}
__device__ __forceinline__ float warp_max(float v) {
#pragma unroll
    for (int o = 16; o > 0; o >>= 1) v = fmaxf(v, __shfl_xor_sync(0xffffffffu, v, o));
    return v;
}

template <int N>
__device__ __forceinline__ void layernorm_row(float (&v)[N], const bool (&valid)[N]) {
    float s = 0.f;
#pragma unroll
    for (int i = 0; i < N; i++) s += valid[i] ? v[i] : 0.f;
    s = warp_sum(s);
    const float mean = s * (1.0f / 576.0f);
    float q = 0.f;
#pragma unroll
    for (int i = 0; i < N; i++) { float d = v[i] - mean; q += valid[i] ? d * d : 0.f; }
    q = warp_sum(q);
    const float m_b = bf16r(__fdiv_rn(s, 576.0f));
    const float var_b = bf16r(__fdiv_rn(q, 576.0f));
    const float sd = bf16r(__fsqrt_rn(bf16r(var_b + 1e-5f)));
#pragma unroll
    for (int i = 0; i < N; i++) v[i] = bf16r(__fdiv_rn(bf16r(v[i] - m_b), sd));
}

struct Params {
    const __nv_bfloat16* x;
    const __nv_bfloat16* k;
    const __nv_bfloat16* v;
    __nv_bfloat16* out;
};

__global__ void __launch_bounds__(288, 1)
fused_decode_kernel(const __grid_constant__ CUtensorMap map_wq, const __grid_constant__ CUtensorMap map_wo,
                    const __grid_constant__ CUtensorMap map_w1, const __grid_constant__ CUtensorMap map_w2,
                    const Params prm)
{
    extern __shared__ __align__(1024) unsigned char smem[];
    const uint32_t sb = smem_u32(smem);
    const int tid = threadIdx.x, warp = tid >> 5, lane = tid & 31;
    const int c = blockIdx.x >> 3;
    const int r = blockIdx.x & 7;
    const uint32_t bar_full = sb + SM_BAR, bar_empty = sb + SM_BAR + NS * 8;

    if (warp == 8) {
        unsigned long long t0 = 0;
        int i = 0, slot = 0; uint32_t ph = 1; long long bytes_before = 0;
        const char* kbase = (const char*)prm.k + ((size_t)(r * HKV + c) * SK + (SK - WIN)) * (DH * 2);
        const char* vbase = (const char*)prm.v + ((size_t)(r * HKV + c) * SK + (SK - WIN)) * (DH * 2);
        const int w1col = c * 288 + (r < 4 ? r * 40 : 160 + (r - 4) * 32);
        auto issue = [&](int i, int slot) -> uint32_t {
            const uint32_t dst = sb + SM_RING + slot * SLOT, fb = bar_full + slot * 8;
            uint32_t bytes;
            if (i < IT_K) {
                bytes = 192 * 64;
                mbar_expect_tx(fb, bytes);
                tma_2d(dst, &map_wq, c * 256 + r * 32, i * 192, fb);
            } else if (i < IT_V) {
                bytes = SLOT;
                mbar_expect_tx(fb, bytes);
                bulk_g2s(dst, kbase + (size_t)(i - IT_K) * SLOT, bytes, fb);
            } else if (i < IT_WO) {
                bytes = SLOT;
                mbar_expect_tx(fb, bytes);
                bulk_g2s(dst, vbase + (size_t)(i - IT_V) * SLOT, bytes, fb);
            } else if (i < IT_W1) {
                const int j = i - IT_WO, nb = j < 2 ? 3 : 2;
                bytes = nb * 32 * 144;
                mbar_expect_tx(fb, bytes);
                for (int u = 0; u < nb; u++) tma_2d(dst + u * 32 * 144, &map_wo, r * 72, c * 256 + j * 96 + u * 32, fb);
            } else if (i < IT_W2) {
                bytes = 192 * 80;
                mbar_expect_tx(fb, bytes);
                tma_2d(dst, &map_w1, w1col, (i - IT_W1) * 192, fb);
            } else {
                const int j = i - IT_W2;
                bytes = 96 * 144;
                mbar_expect_tx(fb, bytes);
                for (int u = 0; u < 3; u++) tma_2d(dst + u * 32 * 144, &map_w2, r * 72, c * 288 + j * 96 + u * 32, fb);
            }
            return bytes;
        };
        if (lane == 0) {
            t0 = gtime();
            DBG_T(0);
            for (int k = 0; k < NS; k++) { mbar_init(bar_full + k * 8, 1); mbar_init(bar_empty + k * 8, 4); }
            asm volatile("fence.mbarrier_init.release.cluster;" ::: "memory");
            asm volatile("fence.proxy.async.shared::cta;" ::: "memory");
            while (i < NS && bytes_before <= PACE_LEAD) {
                bytes_before += issue(i, slot);
                i++;
                if (++slot == NS) { slot = 0; ph ^= 1; }
            }
        }
        __syncwarp();
        asm volatile("bar.sync 0;" ::: "memory");
        if (lane == 0) {
            for (; i < N_ITEMS; i++) {
                mbar_wait(bar_empty + slot * 8, ph);
                const long long lead = bytes_before - PACE_LEAD;
                if (lead > 0) {
                    const unsigned long long tgt = t0 + (unsigned long long)((lead * PACE_PS_PER_KB) >> 10) / 1000ull;
                    while (gtime() < tgt) { }
                }
                bytes_before += issue(i, slot);
                if (++slot == NS) { slot = 0; ph ^= 1; }
            }
            DBG_T(1);
        }
        return;
    }

    const int g = lane >> 2, t = lane & 3;
    uint32_t epoch;
    asm volatile("ld.relaxed.gpu.global.u32 %0, [%1];" : "=r"(epoch) : "l"(&g_epoch) : "memory");
    float xv[18];
    {
        const uint32_t* xr = (const uint32_t*)(prm.x + warp * DM);
#pragma unroll
        for (int j = 0; j < 9; j++) { uint32_t w = __ldg(xr + j * 32 + lane); xv[2 * j] = bf_lo(w); xv[2 * j + 1] = bf_hi(w); }
    }
    const int pb = c >> 1, pcol = 72 * r + 36 * (c & 1) + 4 * (tid >> 4);
    uint2 xres = make_uint2(0, 0);
    if (tid < 144) xres = __ldg((const uint2*)(prm.x + pb * DM + pcol));
    epoch += 1;
    const uint32_t tag16 = epoch & 0xffffu, tag2 = epoch & 3u;

    {
        bool valid[18];
#pragma unroll
        for (int i = 0; i < 18; i++) valid[i] = true;
        layernorm_row<18>(xv, valid);
        uint32_t* act = (uint32_t*)(smem + SM_ACT) + warp * (ACT_PITCH / 2);
#pragma unroll
        for (int j = 0; j < 9; j++) act[j * 32 + lane] = bf16_bits(xv[2 * j]) | (bf16_bits(xv[2 * j + 1]) << 16);
    }
    asm volatile("bar.sync 0;" ::: "memory");
    DBG_T(2);

    {
        const int m = warp & 1, kq = warp >> 1;
#pragma unroll
        for (int j = 0; j < 3; j++) mbar_wait(bar_full + j * 8, 0);
        float acc[4] = {0.f, 0.f, 0.f, 0.f};
        const int lrow = (lane & 7) + ((lane >> 4) & 1) * 8;
        const int lchunk = m * 2 + ((lane >> 3) & 1);
#pragma unroll
        for (int s = 0; s < 9; s++) {
            const int ks = kq * 9 + s;
            const int item = ks / 12, row = (ks % 12) * 16 + lrow;
            uint32_t a0, a1, a2, a3, b0, b1;
            ldsm_x4_t(a0, a1, a2, a3, sb + SM_RING + item * SLOT + row * 64 + ((lchunk ^ ((row >> 1) & 3)) << 4));
            ldsm_x2(b0, b1, sb + SM_ACT + (lane & 7) * (ACT_PITCH * 2) + (ks * 16 + ((lane >> 3) & 1) * 8) * 2);
            mma16816(acc, a0, a1, a2, a3, b0, b1);
        }
        float* red = (float*)(smem + SM_RED);
        red[(kq * 8 + 2 * t) * 32 + m * 16 + g] = acc[0];
        red[(kq * 8 + 2 * t + 1) * 32 + m * 16 + g] = acc[1];
        red[(kq * 8 + 2 * t) * 32 + m * 16 + g + 8] = acc[2];
        red[(kq * 8 + 2 * t + 1) * 32 + m * 16 + g + 8] = acc[3];
        cons_sync();
        if (warp < 4 && lane == 0) { mbar_arrive(bar_empty + 0); mbar_arrive(bar_empty + 8); mbar_arrive(bar_empty + 16); }
        const float s = (red[(0 * 8 + warp) * 32 + lane] + red[(1 * 8 + warp) * 32 + lane]) +
                        (red[(2 * 8 + warp) * 32 + lane] + red[(3 * 8 + warp) * 32 + lane]);
        st_pub(&g_scr.q[c][warp][r * 32 + lane], (bf16_bits(s) << 16) | tag16);
        if (tid < 64) {
            uint4 v = poll_bf16x4(&g_scr.q[c][r][tid * 4], tag16);
            *(uint2*)(smem + SM_QS + tid * 8) = make_uint2(pack_hi16(v.x, v.y), pack_hi16(v.z, v.w));
        }
        cons_sync();
    }
    DBG_T(3);

    {
        uint32_t bq[16];
        {
            const int pi = (g >> 1) & 1, h = g & 1;
#pragma unroll
            for (int j = 0; j < 4; j++) {
                uint4 v = lds128(sb + SM_QS + h * 256 + (4 * (j ^ pi) + t) * 16);
                if (g >= 4) v = make_uint4(0, 0, 0, 0);
                bq[4 * j] = v.x; bq[4 * j + 1] = v.y; bq[4 * j + 2] = v.z; bq[4 * j + 3] = v.w;
            }
        }
        const int pig = g & 1;
        int slot = (IT_K + (warp >> 2)) % NS; uint32_t ph = 0;
        const uint32_t rowoff = ((warp & 3) * 16 + g) * 256;
        unsigned short* sc = (unsigned short*)(smem + SM_SC);
        for (int kt = warp >> 2; kt < 32; kt += 2) {
            mbar_wait(bar_full + slot * 8, ph);
            const uint32_t base = sb + SM_RING + slot * SLOT + rowoff;
            uint4 X[4], Y[4];
#pragma unroll
            for (int j = 0; j < 4; j++) {
                const uint32_t a = base + (4 * (j ^ pig) + t) * 16;
                X[j] = lds128(a); Y[j] = lds128(a + 2048);
            }
            float ca[4] = {0.f, 0.f, 0.f, 0.f}, cb[4] = {0.f, 0.f, 0.f, 0.f};
#pragma unroll
            for (int j = 0; j < 4; j++) {
                mma16816(ca, X[j].x, Y[j].x, X[j].y, Y[j].y, bq[4 * j], bq[4 * j + 1]);
                mma16816(cb, X[j].z, Y[j].z, X[j].w, Y[j].w, bq[4 * j + 2], bq[4 * j + 3]);
            }
            __syncwarp();
            if (lane == 0) mbar_arrive(bar_empty + slot * 8);
            if (t == pig) {
                const int key = kt * 64 + (warp & 3) * 16 + g;
                const float scale = 0.08838834764831845f;
                sc[key] = (unsigned short)bf16_bits(bf16r(ca[0] + cb[0]) * scale);
                sc[2048 + key] = (unsigned short)bf16_bits(bf16r(ca[1] + cb[1]) * scale);
                sc[key + 8] = (unsigned short)bf16_bits(bf16r(ca[2] + cb[2]) * scale);
                sc[2048 + key + 8] = (unsigned short)bf16_bits(bf16r(ca[3] + cb[3]) * scale);
            }
            slot += 2; if (slot >= NS) { slot -= NS; ph ^= 1; }
        }
    }
    cons_sync();
    DBG_T(4);

    {
        const int h = tid >> 7, idx = tid & 127;
        const uint32_t a = sb + SM_SC + h * 4096 + idx * 32;
        uint4 u0 = lds128(a), u1 = lds128(a + 16);
        float e[16];
        e[0] = bf_lo(u0.x); e[1] = bf_hi(u0.x); e[2] = bf_lo(u0.y); e[3] = bf_hi(u0.y);
        e[4] = bf_lo(u0.z); e[5] = bf_hi(u0.z); e[6] = bf_lo(u0.w); e[7] = bf_hi(u0.w);
        e[8] = bf_lo(u1.x); e[9] = bf_hi(u1.x); e[10] = bf_lo(u1.y); e[11] = bf_hi(u1.y);
        e[12] = bf_lo(u1.z); e[13] = bf_hi(u1.z); e[14] = bf_lo(u1.w); e[15] = bf_hi(u1.w);
        float mx = e[0];
#pragma unroll
        for (int i = 1; i < 16; i++) mx = fmaxf(mx, e[i]);
        mx = warp_max(mx);
        float* stat = (float*)(smem + SM_STAT);
        if (lane == 0) stat[warp] = mx;
        cons_sync();
        mx = fmaxf(fmaxf(stat[h * 4], stat[h * 4 + 1]), fmaxf(stat[h * 4 + 2], stat[h * 4 + 3]));
        float sum = 0.f;
#pragma unroll
        for (int i = 0; i < 16; i++) { e[i] = exp2f((e[i] - mx) * 1.4426950408889634f); sum += e[i]; }
        sum = warp_sum(sum);
        if (lane == 0) stat[8 + warp] = sum;
        cons_sync();
        sum = (stat[8 + h * 4] + stat[8 + h * 4 + 1]) + (stat[8 + h * 4 + 2] + stat[8 + h * 4 + 3]);
        uint32_t w[8];
#pragma unroll
        for (int i = 0; i < 8; i++)
            w[i] = bf16_bits(__fdiv_rn(e[2 * i], sum)) | (bf16_bits(__fdiv_rn(e[2 * i + 1], sum)) << 16);
        *(uint4*)(smem + SM_SC + h * 4096 + idx * 32) = make_uint4(w[0], w[1], w[2], w[3]);
        *(uint4*)(smem + SM_SC + h * 4096 + idx * 32 + 16) = make_uint4(w[4], w[5], w[6], w[7]);
        cons_sync();
    }
    DBG_T(5);

    {
        float acc[2][4][4];
#pragma unroll
        for (int a = 0; a < 2; a++)
#pragma unroll
            for (int b = 0; b < 4; b++)
#pragma unroll
                for (int d = 0; d < 4; d++) acc[a][b][d] = 0.f;
        const int first = IT_V + (warp >> 2);
        int slot = first % NS; uint32_t ph = (first / NS) & 1;
        const bool bvalid = (g >> 1) == t;
        const uint32_t paddr = sb + SM_SC + (g & 1) * 4096 + ((warp & 3) * 16 + 4 * t) * 2;
        const uint32_t rowoff = ((warp & 3) * 16 + 4 * t) * 256 + (g ^ (2 * t)) * 16;
        for (int vt = warp >> 2; vt < 32; vt += 2) {
            uint2 pbv = lds64(paddr + vt * 128);
            const uint32_t b0 = bvalid ? pbv.x : 0u, b1 = bvalid ? pbv.y : 0u;
            mbar_wait(bar_full + slot * 8, ph);
            const uint32_t base = sb + SM_RING + slot * SLOT + rowoff;
            uint4 X[2][4];
#pragma unroll
            for (int hf = 0; hf < 2; hf++)
#pragma unroll
                for (int i = 0; i < 4; i++) X[hf][i] = lds128(base + i * 256 + hf * 128);
#pragma unroll
            for (int hf = 0; hf < 2; hf++) {
                const uint32_t x0[4] = {X[hf][0].x, X[hf][0].y, X[hf][0].z, X[hf][0].w};
                const uint32_t x1[4] = {X[hf][1].x, X[hf][1].y, X[hf][1].z, X[hf][1].w};
                const uint32_t x2[4] = {X[hf][2].x, X[hf][2].y, X[hf][2].z, X[hf][2].w};
                const uint32_t x3[4] = {X[hf][3].x, X[hf][3].y, X[hf][3].z, X[hf][3].w};
#pragma unroll
                for (int m = 0; m < 4; m++) {
                    mma16816(acc[hf][m], __byte_perm(x0[m], x1[m], 0x5410), __byte_perm(x0[m], x1[m], 0x7632),
                             __byte_perm(x2[m], x3[m], 0x5410), __byte_perm(x2[m], x3[m], 0x7632), b0, b1);
                }
            }
            __syncwarp();
            if (lane == 0) mbar_arrive(bar_empty + slot * 8);
            slot += 2; if (slot >= NS) { slot -= NS; ph ^= 1; }
        }
        DBG_T(6);
        float* red = (float*)(smem + SM_RED) + (warp * 4 + t) * 256;
        const int cch = g ^ (2 * t);
#pragma unroll
        for (int hf = 0; hf < 2; hf++)
#pragma unroll
            for (int h = 0; h < 2; h++) {
                float* d = red + h * 128 + (cch + 8 * hf) * 8;
                *(float4*)d = make_float4(acc[hf][0][h], acc[hf][0][2 + h], acc[hf][1][h], acc[hf][1][2 + h]);
                *(float4*)(d + 4) = make_float4(acc[hf][2][h], acc[hf][2][2 + h], acc[hf][3][h], acc[hf][3][2 + h]);
            }
        cons_sync();
        const float* rr = (const float*)(smem + SM_RED) + tid;
        float s0 = 0.f, s1 = 0.f, s2 = 0.f, s3 = 0.f;
#pragma unroll
        for (int p = 0; p < 32; p += 4) { s0 += rr[p * 256]; s1 += rr[(p + 1) * 256]; s2 += rr[(p + 2) * 256]; s3 += rr[(p + 3) * 256]; }
        st_pub(&g_scr.o[c][r][tid], (bf16_bits((s0 + s1) + (s2 + s3)) << 16) | tag16);
#pragma unroll
        for (int u = 0; u < 2; u++) {
            const int v = tid + 256 * u, b = v >> 6, k4 = (v & 63) * 4;
            uint4 w = poll_bf16x4(&g_scr.o[c][b][k4], tag16);
            *(uint2*)(smem + SM_SC + (b * OALL_PITCH + k4) * 2) = make_uint2(pack_hi16(w.x, w.y), pack_hi16(w.z, w.w));
        }
        cons_sync();
    }
    DBG_T(7);

    const int lrow = (lane & 7) + ((lane >> 4) & 1) * 8;
    const int lcol = ((lane >> 3) & 1) * 16;
    if (warp < 5) {
#pragma unroll
        for (int j = 0; j < 3; j++) mbar_wait(bar_full + ((IT_WO + j) % NS) * 8, ((IT_WO + j) / NS) & 1);
        float ca[4] = {0.f, 0.f, 0.f, 0.f}, cb[4] = {0.f, 0.f, 0.f, 0.f};
#pragma unroll
        for (int ks = 0; ks < 16; ks += 2) {
            uint32_t b0, b1, b2, b3, a0, a1, a2, a3;
            ldsm_x4(b0, b1, b2, b3, sb + SM_SC + (lane & 7) * (OALL_PITCH * 2) + (ks * 16 + (lane >> 3) * 8) * 2);
            {
                const int row = ks * 16;
                ldsm_x4_t(a0, a1, a2, a3, sb + SM_RING + ((IT_WO + row / 96) % NS) * SLOT + (row % 96 + lrow) * 144 + warp * 32 + lcol);
                mma16816(ca, a0, a1, a2, a3, b0, b1);
            }
            {
                const int row = ks * 16 + 16;
                ldsm_x4_t(a0, a1, a2, a3, sb + SM_RING + ((IT_WO + row / 96) % NS) * SLOT + (row % 96 + lrow) * 144 + warp * 32 + lcol);
                mma16816(cb, a0, a1, a2, a3, b2, b3);
            }
        }
        const int col = warp * 16 + g;
        uint32_t* dst = &g_scr.ap[r][c][0][0];
        st_pub(dst + (2 * t) * 72 + col, (__float_as_uint(ca[0] + cb[0]) & ~3u) | tag2);
        st_pub(dst + (2 * t + 1) * 72 + col, (__float_as_uint(ca[1] + cb[1]) & ~3u) | tag2);
        if (col + 8 < 72) {
            st_pub(dst + (2 * t) * 72 + col + 8, (__float_as_uint(ca[2] + cb[2]) & ~3u) | tag2);
            st_pub(dst + (2 * t + 1) * 72 + col + 8, (__float_as_uint(ca[3] + cb[3]) & ~3u) | tag2);
        }
    }
    DBG_T(8);
    float hres[4] = {0.f, 0.f, 0.f, 0.f};
    if (warp < 5) {
        float s[4] = {0.f, 0.f, 0.f, 0.f};
        if (tid < 144) {
            uint4 w = poll_f32x4(&g_scr.ap[r][tid & 15][pb][36 * (c & 1) + 4 * (tid >> 4)], tag2);
            s[0] = __uint_as_float(w.x & ~3u); s[1] = __uint_as_float(w.y & ~3u);
            s[2] = __uint_as_float(w.z & ~3u); s[3] = __uint_as_float(w.w & ~3u);
        }
        __syncwarp();
#pragma unroll
        for (int o = 1; o < 16; o <<= 1)
#pragma unroll
            for (int i = 0; i < 4; i++) s[i] += __shfl_xor_sync(0xffffffffu, s[i], o);
        if (tid < 144 && (tid & 15) == 0) {
            hres[0] = bf16r(bf_lo(xres.x) + bf16r(s[0])); hres[1] = bf16r(bf_hi(xres.x) + bf16r(s[1]));
            hres[2] = bf16r(bf_lo(xres.y) + bf16r(s[2])); hres[3] = bf16r(bf_hi(xres.y) + bf16r(s[3]));
            st_pub4(&g_scr.h[pb][pcol], make_uint4(__float_as_uint(hres[0]) | tag16, __float_as_uint(hres[1]) | tag16,
                                                   __float_as_uint(hres[2]) | tag16, __float_as_uint(hres[3]) | tag16));
        }
    }
    {
        float hv[20]; bool valid[20];
#pragma unroll
        for (int j = 0; j < 5; j++) {
            const bool ok = (j < 4) || (lane < 16);
            uint4 w = make_uint4(0, 0, 0, 0);
            if (ok) w = poll_bf16x4(&g_scr.h[warp][(j * 32 + lane) * 4], tag16);
            hv[4 * j] = bf_hi(w.x); hv[4 * j + 1] = bf_hi(w.y); hv[4 * j + 2] = bf_hi(w.z); hv[4 * j + 3] = bf_hi(w.w);
            valid[4 * j] = valid[4 * j + 1] = valid[4 * j + 2] = valid[4 * j + 3] = ok;
        }
        __syncwarp();
        layernorm_row<20>(hv, valid);
#pragma unroll
        for (int j = 0; j < 5; j++) {
            if (valid[4 * j]) {
                *(uint2*)(smem + SM_ACT + (warp * ACT_PITCH + (j * 32 + lane) * 4) * 2) =
                    make_uint2(pack_hi16(__float_as_uint(hv[4 * j]), __float_as_uint(hv[4 * j + 1])),
                               pack_hi16(__float_as_uint(hv[4 * j + 2]), __float_as_uint(hv[4 * j + 3])));
            }
        }
        cons_sync();
    }
    DBG_T(9);

    {
#pragma unroll
        for (int j = 0; j < 3; j++) mbar_wait(bar_full + ((IT_W1 + j) % NS) * 8, ((IT_W1 + j) / NS) & 1);
        float acc[3][4];
#pragma unroll
        for (int m = 0; m < 3; m++) { acc[m][0] = acc[m][1] = acc[m][2] = acc[m][3] = 0.f; }
        for (int ks = warp; ks < 36; ks += 8) {
            uint32_t b0, b1;
            ldsm_x2(b0, b1, sb + SM_ACT + (lane & 7) * (ACT_PITCH * 2) + (ks * 16 + ((lane >> 3) & 1) * 8) * 2);
            const int item = IT_W1 + ks / 12;
            const uint32_t base = sb + SM_RING + (item % NS) * SLOT + ((ks % 12) * 16 + lrow) * 80 + lcol;
#pragma unroll
            for (int m = 0; m < 3; m++) {
                uint32_t a0, a1, a2, a3;
                ldsm_x4_t(a0, a1, a2, a3, base + m * 32);
                mma16816(acc[m], a0, a1, a2, a3, b0, b1);
            }
        }
        float* red = (float*)(smem + SM_RED);
#pragma unroll
        for (int m = 0; m < 3; m++) {
            red[(warp * 8 + 2 * t) * 48 + m * 16 + g] = acc[m][0];
            red[(warp * 8 + 2 * t + 1) * 48 + m * 16 + g] = acc[m][1];
            red[(warp * 8 + 2 * t) * 48 + m * 16 + g + 8] = acc[m][2];
            red[(warp * 8 + 2 * t + 1) * 48 + m * 16 + g + 8] = acc[m][3];
        }
        cons_sync();
        const int nv = r < 4 ? 40 : 32, start = r < 4 ? r * 40 : 160 + (r - 4) * 32;
        for (int o = tid; o < 8 * nv; o += 256) {
            const int b = o / nv, col = o - b * nv;
            float s = 0.f;
#pragma unroll
            for (int w = 0; w < 8; w++) s += red[(w * 8 + b) * 48 + col];
            s = bf16r(s);
            s = (s != s) ? s : fmaxf(s, 0.f);
            st_pub(&g_scr.h1[c][b][start + col], __float_as_uint(s) | tag16);
        }
        for (int v = tid; v < 576; v += 256) {
            const int b = v / 72, k4 = (v - b * 72) * 4;
            uint4 w = poll_bf16x4(&g_scr.h1[c][b][k4], tag16);
            *(uint2*)(smem + SM_SC + (b * H1_PITCH + k4) * 2) = make_uint2(pack_hi16(w.x, w.y), pack_hi16(w.z, w.w));
        }
        cons_sync();
    }
    DBG_T(10);

    if (warp < 5) {
        float ca[4] = {0.f, 0.f, 0.f, 0.f}, cb[4] = {0.f, 0.f, 0.f, 0.f};
#pragma unroll
        for (int j = 0; j < 3; j++) {
            mbar_wait(bar_full + ((IT_W2 + j) % NS) * 8, ((IT_W2 + j) / NS) & 1);
#pragma unroll
            for (int u = 0; u < 6; u += 2) {
                const int ks = j * 6 + u;
                uint32_t b0, b1, b2, b3, a0, a1, a2, a3;
                ldsm_x4(b0, b1, b2, b3, sb + SM_SC + (lane & 7) * (H1_PITCH * 2) + (ks * 16 + (lane >> 3) * 8) * 2);
                const uint32_t base = sb + SM_RING + ((IT_W2 + j) % NS) * SLOT + (u * 16 + lrow) * 144 + warp * 32 + lcol;
                ldsm_x4_t(a0, a1, a2, a3, base);
                mma16816(ca, a0, a1, a2, a3, b0, b1);
                ldsm_x4_t(a0, a1, a2, a3, base + 16 * 144);
                mma16816(cb, a0, a1, a2, a3, b2, b3);
            }
        }
        const int col = warp * 16 + g;
        uint32_t* dst = &g_scr.fp[r][c][0][0];
        st_pub(dst + (2 * t) * 72 + col, (__float_as_uint(ca[0] + cb[0]) & ~3u) | tag2);
        st_pub(dst + (2 * t + 1) * 72 + col, (__float_as_uint(ca[1] + cb[1]) & ~3u) | tag2);
        if (col + 8 < 72) {
            st_pub(dst + (2 * t) * 72 + col + 8, (__float_as_uint(ca[2] + cb[2]) & ~3u) | tag2);
            st_pub(dst + (2 * t + 1) * 72 + col + 8, (__float_as_uint(ca[3] + cb[3]) & ~3u) | tag2);
        }
        DBG_T(11);
        float s[4] = {0.f, 0.f, 0.f, 0.f};
        if (tid < 144) {
            uint4 w = poll_f32x4(&g_scr.fp[r][tid & 15][pb][36 * (c & 1) + 4 * (tid >> 4)], tag2);
            s[0] = __uint_as_float(w.x & ~3u); s[1] = __uint_as_float(w.y & ~3u);
            s[2] = __uint_as_float(w.z & ~3u); s[3] = __uint_as_float(w.w & ~3u);
        }
        __syncwarp();
#pragma unroll
        for (int o = 1; o < 16; o <<= 1)
#pragma unroll
            for (int i = 0; i < 4; i++) s[i] += __shfl_xor_sync(0xffffffffu, s[i], o);
        if (tid < 144 && (tid & 15) == 0) {
            uint2 o;
            o.x = bf16_bits(hres[0] + bf16r(s[0])) | (bf16_bits(hres[1] + bf16r(s[1])) << 16);
            o.y = bf16_bits(hres[2] + bf16r(s[2])) | (bf16_bits(hres[3] + bf16r(s[3])) << 16);
            *(uint2*)(prm.out + pb * DM + pcol) = o;
        }
        if (blockIdx.x == 0 && tid == 0) g_epoch = epoch;
        DBG_T(12);
    }
}

typedef CUresult (*EncodeTiledFn)(CUtensorMap*, CUtensorMapDataType, cuuint32_t, void*, const cuuint64_t*, const cuuint64_t*,
                                  const cuuint32_t*, const cuuint32_t*, CUtensorMapInterleave, CUtensorMapSwizzle,
                                  CUtensorMapL2promotion, CUtensorMapFloatOOBfill);

void make_map(EncodeTiledFn fn, CUtensorMap* m, const void* ptr, uint64_t cols, uint64_t rows, uint32_t bc, uint32_t br,
              CUtensorMapSwizzle sw) {
    cuuint64_t dims[2] = {cols, rows};
    cuuint64_t strides[1] = {cols * 2};
    cuuint32_t box[2] = {bc, br};
    cuuint32_t es[2] = {1, 1};
    fn(m, CU_TENSOR_MAP_DATA_TYPE_BFLOAT16, 2, const_cast<void*>(ptr), dims, strides, box, es, CU_TENSOR_MAP_INTERLEAVE_NONE, sw,
       CU_TENSOR_MAP_L2_PROMOTION_L2_256B, CU_TENSOR_MAP_FLOAT_OOB_FILL_NONE);
}

}

extern "C" void kernel_launch(void* const* d_in, const int* in_sizes, int n_in, void* d_out, int out_size) {
    (void)in_sizes; (void)n_in; (void)out_size;
    static EncodeTiledFn enc = nullptr;
    if (!enc) {
        void* fn = nullptr;
        cudaDriverEntryPointQueryResult qr;
        cudaGetDriverEntryPoint("cuTensorMapEncodeTiled", &fn, cudaEnableDefault, &qr);
        enc = (EncodeTiledFn)fn;
        cudaFuncSetAttribute(fused_decode_kernel, cudaFuncAttributeMaxDynamicSharedMemorySize, SM_TOTAL);
    }
    CUtensorMap mq, mo, m1, m2;
    make_map(enc, &mq, d_in[3], 4096, DM, 32, 192, CU_TENSOR_MAP_SWIZZLE_64B);
    make_map(enc, &mo, d_in[4], DM, 4096, 72, 32, CU_TENSOR_MAP_SWIZZLE_NONE);
    make_map(enc, &m1, d_in[6], DFF, DM, 40, 192, CU_TENSOR_MAP_SWIZZLE_NONE);
    make_map(enc, &m2, d_in[7], DM, DFF, 72, 32, CU_TENSOR_MAP_SWIZZLE_NONE);
    Params p;
    p.x = (const __nv_bfloat16*)d_in[0];
    p.k = (const __nv_bfloat16*)d_in[1];
    p.v = (const __nv_bfloat16*)d_in[2];
    p.out = (__nv_bfloat16*)d_out;
    fused_decode_kernel<<<NCTA, 288, SM_TOTAL, cudaStreamPerThread>>>(mq, mo, m1, m2, p);
}
```

```cpp
#include <cuda_runtime.h>
#include <cuda_bf16.h>
#include <cuda.h>
#include <stdint.h>

namespace {

constexpr int NB = 8;
constexpr int DM = 576;
constexpr int HKV = 16;
constexpr int DH = 128;
constexpr int SK = 8192;
constexpr int WIN = 2048;
constexpr int DFF = 4608;
constexpr int NCL = 8;
constexpr int CS = 8;
constexpr int NCTA = NCL * CS;

constexpr int SLOT = 16384;
constexpr int NS = 12;
constexpr int IT_KA = 5, IT_VA = 37, IT_WOA = 69, IT_KB = 72, IT_VB = 104, IT_FIFO_END = 128;
constexpr int CHUNK = 96 * 144;
constexpr int TAIL = 4 * SLOT;
constexpr int TAIL_W1 = TAIL + 256 * 144;

#define INFLIGHT 8

constexpr int PITCH = 584;
constexpr int OPITCH = 264;
constexpr int SM_R1 = NS * SLOT;
constexpr int SM_R2 = SM_R1 + NB * PITCH * 2;
constexpr int SM_R3 = SM_R2 + NB * PITCH * 2;
constexpr int SM_QS = SM_R3 + NB * PITCH * 2;
constexpr int SM_HS = SM_QS + 1024;
constexpr int SM_OL = SM_HS + 288;
constexpr int SM_STAT = SM_OL + 512;
constexpr int SM_BAR = SM_STAT + 64;
constexpr int BAR_FULL = 0, BAR_EMPTY = 12, BAR_TW = 24, BAR_Q = 39, BAR_OA = 40, BAR_OB = 41, BAR_H = 42, BAR_H1 = 43,
              BAR_WOFREE = 44, NBAR = 45;
constexpr int SM_TOTAL = SM_BAR + NBAR * 8;
static_assert(SM_TOTAL <= 232448, "smem");
static_assert(2 * NB * OPITCH * 2 <= NB * PITCH * 2, "o_all");

constexpr uint32_t SENT = 0xffffffffu;

struct Scratch {
    uint32_t ap[CS][NCL][576];
    uint32_t fp[CS][NCL][576];
};
__device__ __align__(128) Scratch g_scr;
__device__ uint32_t g_cnt;

#define DBG_T(i) do { } while (0)

__device__ __forceinline__ uint32_t smem_u32(const void* p) { return (uint32_t)__cvta_generic_to_shared(p); }
__device__ __forceinline__ unsigned long long gtime() {
    unsigned long long t; asm volatile("mov.u64 %0, %globaltimer;" : "=l"(t)); return t;
}
__device__ __forceinline__ void mbar_init(uint32_t bar, uint32_t cnt) {
    asm volatile("mbarrier.init.shared::cta.b64 [%0], %1;" ::"r"(bar), "r"(cnt) : "memory");
}
__device__ __forceinline__ void mbar_expect_tx(uint32_t bar, uint32_t bytes) {
    asm volatile("mbarrier.arrive.expect_tx.shared::cta.b64 _, [%0], %1;" ::"r"(bar), "r"(bytes) : "memory");
}
__device__ __forceinline__ void mbar_arrive(uint32_t bar) {
    asm volatile("mbarrier.arrive.shared::cta.b64 _, [%0];" ::"r"(bar) : "memory");
}
__device__ __forceinline__ bool mbar_try(uint32_t bar, uint32_t parity) {
    uint32_t ok;
    asm volatile("{\n.reg .pred p;\nmbarrier.try_wait.parity.shared::cta.b64 p, [%1], %2;\nselp.u32 %0, 1, 0, p;\n}"
                 : "=r"(ok) : "r"(bar), "r"(parity) : "memory");
    return ok != 0;
}
__device__ __forceinline__ void mbar_wait(uint32_t bar, uint32_t parity) {
    uint32_t spins = 0;
    while (!mbar_try(bar, parity)) {
        if (++spins > (1u << 22)) __trap();
    }
}
__device__ __forceinline__ bool mbar_try_cl(uint32_t bar, uint32_t parity) {
    uint32_t ok;
    asm volatile("{\n.reg .pred p;\nmbarrier.try_wait.parity.acquire.cluster.shared::cta.b64 p, [%1], %2;\nselp.u32 %0, 1, 0, p;\n}"
                 : "=r"(ok) : "r"(bar), "r"(parity) : "memory");
    return ok != 0;
}
__device__ __forceinline__ void mbar_wait_cl(uint32_t bar) {
    uint32_t spins = 0;
    while (!mbar_try_cl(bar, 0)) {
        if (++spins > (1u << 22)) __trap();
    }
}
__device__ __forceinline__ void bulk_g2s(uint32_t dst, const void* src, uint32_t bytes, uint32_t bar, uint64_t pol) {
    asm volatile("cp.async.bulk.shared::cluster.global.mbarrier::complete_tx::bytes.L2::cache_hint [%0], [%1], %2, [%3], %4;"
                 ::"r"(dst), "l"(src), "r"(bytes), "r"(bar), "l"(pol) : "memory");
}
__device__ __forceinline__ void tma_2d(uint32_t dst, const CUtensorMap* map, int x, int y, uint32_t bar, uint64_t pol) {
    asm volatile("cp.async.bulk.tensor.2d.shared::cluster.global.mbarrier::complete_tx::bytes.L2::cache_hint [%0], [%1, {%3, %4}], [%2], %5;"
                 ::"r"(dst), "l"(map), "r"(bar), "r"(x), "r"(y), "l"(pol) : "memory");
}
__device__ __forceinline__ void cons_sync() { asm volatile("bar.sync 1, 256;" ::: "memory"); }
__device__ __forceinline__ uint32_t mapa(uint32_t a, uint32_t rank) {
    uint32_t r; asm("mapa.shared::cluster.u32 %0, %1, %2;" : "=r"(r) : "r"(a), "r"(rank)); return r;
}
__device__ __forceinline__ void st_async4(uint32_t addr, uint4 v, uint32_t bar) {
    asm volatile("st.async.weak.shared::cluster.mbarrier::complete_tx::bytes.v4.b32 [%0], {%1,%2,%3,%4}, [%5];"
                 ::"r"(addr), "r"(v.x), "r"(v.y), "r"(v.z), "r"(v.w), "r"(bar) : "memory");
}
__device__ __forceinline__ uint4 lds128(uint32_t a) {
    uint4 v; asm volatile("ld.shared.v4.u32 {%0,%1,%2,%3}, [%4];" : "=r"(v.x), "=r"(v.y), "=r"(v.z), "=r"(v.w) : "r"(a)); return v;
}
__device__ __forceinline__ uint2 lds64(uint32_t a) {
    uint2 v; asm volatile("ld.shared.v2.u32 {%0,%1}, [%2];" : "=r"(v.x), "=r"(v.y) : "r"(a)); return v;
}
__device__ __forceinline__ void ldsm_x4(uint32_t& r0, uint32_t& r1, uint32_t& r2, uint32_t& r3, uint32_t a) {
    asm volatile("ldmatrix.sync.aligned.m8n8.x4.shared.b16 {%0,%1,%2,%3}, [%4];"
                 : "=r"(r0), "=r"(r1), "=r"(r2), "=r"(r3) : "r"(a));
}
__device__ __forceinline__ void ldsm_x2(uint32_t& r0, uint32_t& r1, uint32_t a) {
    asm volatile("ldmatrix.sync.aligned.m8n8.x2.shared.b16 {%0,%1}, [%2];" : "=r"(r0), "=r"(r1) : "r"(a));
}
__device__ __forceinline__ void ldsm_x4_t(uint32_t& r0, uint32_t& r1, uint32_t& r2, uint32_t& r3, uint32_t a) {
    asm volatile("ldmatrix.sync.aligned.m8n8.x4.trans.shared.b16 {%0,%1,%2,%3}, [%4];"
                 : "=r"(r0), "=r"(r1), "=r"(r2), "=r"(r3) : "r"(a));
}
__device__ __forceinline__ void mma16816(float (&c)[4], uint32_t a0, uint32_t a1, uint32_t a2, uint32_t a3, uint32_t b0, uint32_t b1) {
    asm volatile("mma.sync.aligned.m16n8k16.row.col.f32.bf16.bf16.f32 {%0,%1,%2,%3}, {%4,%5,%6,%7}, {%8,%9}, {%0,%1,%2,%3};"
                 : "+f"(c[0]), "+f"(c[1]), "+f"(c[2]), "+f"(c[3])
                 : "r"(a0), "r"(a1), "r"(a2), "r"(a3), "r"(b0), "r"(b1));
}
__device__ __forceinline__ uint4 ld_poll4(const uint32_t* p) {
    uint4 v;
    asm volatile("ld.relaxed.gpu.global.v4.u32 {%0,%1,%2,%3}, [%4];" : "=r"(v.x), "=r"(v.y), "=r"(v.z), "=r"(v.w) : "l"(p) : "memory");
    return v;
}
__device__ __forceinline__ void st_pub4(uint32_t* p, uint4 v) {
    asm volatile("st.relaxed.gpu.global.v4.u32 [%0], {%1,%2,%3,%4};" ::"l"(p), "r"(v.x), "r"(v.y), "r"(v.z), "r"(v.w) : "memory");
}
__device__ __forceinline__ bool vec_valid(const uint4& v) { return v.x != SENT && v.y != SENT && v.z != SENT && v.w != SENT; }
__device__ __forceinline__ uint32_t f2pub(float f) { uint32_t u = __float_as_uint(f); return u == SENT ? 0x7fffffffu : u; }

__device__ __forceinline__ uint32_t bf16_bits(float f) {
    return (uint32_t)__bfloat16_as_ushort(__float2bfloat16_rn(f));
}
__device__ __forceinline__ uint32_t bf16_pack(float lo, float hi) {
    uint32_t r; asm("cvt.rn.bf16x2.f32 %0, %1, %2;" : "=r"(r) : "f"(hi), "f"(lo)); return r;
}
__device__ __forceinline__ float bf16r(float f) { return __uint_as_float(bf16_bits(f) << 16); }
__device__ __forceinline__ float bf_lo(uint32_t w) { return __uint_as_float(w << 16); }
__device__ __forceinline__ float bf_hi(uint32_t w) { return __uint_as_float(w & 0xffff0000u); }
__device__ __forceinline__ float warp_sum(float v) {
#pragma unroll
    for (int o = 16; o > 0; o >>= 1) v += __shfl_xor_sync(0xffffffffu, v, o);
    return v;
}
__device__ __forceinline__ float warp_max(float v) {
#pragma unroll
    for (int o = 16; o > 0; o >>= 1) v = fmaxf(v, __shfl_xor_sync(0xffffffffu, v, o));
    return v;
}

__device__ __forceinline__ void layernorm_row(uint32_t (&w)[9]) {
    float v[18];
#pragma unroll
    for (int j = 0; j < 9; j++) { v[2 * j] = bf_lo(w[j]); v[2 * j + 1] = bf_hi(w[j]); }
    float s = 0.f;
#pragma unroll
    for (int i = 0; i < 18; i++) s += v[i];
    s = warp_sum(s);
    const float mean = __fdiv_rn(s, 576.0f);
    float q = 0.f;
#pragma unroll
    for (int i = 0; i < 18; i++) { float d = v[i] - mean; q += d * d; }
    q = warp_sum(q);
    const float m_b = bf16r(mean);
    const float var_b = bf16r(__fdiv_rn(q, 576.0f));
    const float sd = bf16r(__fsqrt_rn(bf16r(var_b + 1e-5f)));
#pragma unroll
    for (int j = 0; j < 9; j++)
        w[j] = bf16_pack(__fdiv_rn(bf16r(v[2 * j] - m_b), sd), __fdiv_rn(bf16r(v[2 * j + 1] - m_b), sd));
}

__device__ __forceinline__ int item_slot(int i) { return i < IT_FIFO_END ? i % NS : (i - IT_FIFO_END) & 3; }
__device__ __forceinline__ uint32_t item_par(int i) { return i < IT_FIFO_END ? (i / NS) & 1 : (i < IT_FIFO_END + 4 ? 1u : 0u); }

template <int KSTEPS, typename ChunkAddr>
__device__ __forceinline__ float4 gemv72(uint32_t act, int apitch, ChunkAddr chunk_addr, float* red, int tid) {
    const int warp = tid >> 5, lane = tid & 31, g = lane >> 2, t = lane & 3;
    const int kq = warp & 3, mg = warp >> 2;
    constexpr int KQ = KSTEPS / 4;
    const int lrow = (lane & 7) + ((lane >> 4) & 1) * 8;
    const int lcol = ((lane >> 3) & 1) * 16;
    float acc[3][4];
#pragma unroll
    for (int m = 0; m < 3; m++) { acc[m][0] = acc[m][1] = acc[m][2] = acc[m][3] = 0.f; }
    const uint32_t baddr = act + (lane & 7) * (apitch * 2) + ((lane >> 3) & 1) * 16;
#pragma unroll
    for (int s = 0; s < KQ; s++) {
        const int ks = kq * KQ + s;
        uint32_t b0, b1;
        ldsm_x2(b0, b1, baddr + ks * 32);
        const uint32_t a = chunk_addr(ks / 6) + ((ks % 6) * 16 + lrow) * 144 + lcol + mg * 96;
        uint32_t a0, a1, a2, a3;
        ldsm_x4_t(a0, a1, a2, a3, a);
        mma16816(acc[0], a0, a1, a2, a3, b0, b1);
        ldsm_x4_t(a0, a1, a2, a3, a + 32);
        mma16816(acc[1], a0, a1, a2, a3, b0, b1);
        if (mg == 0) {
            ldsm_x4_t(a0, a1, a2, a3, a + 64);
            mma16816(acc[2], a0, a1, a2, a3, b0, b1);
        }
    }
    float* rp = red + kq * 576;
#pragma unroll
    for (int m = 0; m < 3; m++) {
        const int col = mg * 48 + m * 16 + g;
        if (m < 2 || mg == 0) {
            rp[(2 * t) * 72 + col] = acc[m][0];
            rp[(2 * t + 1) * 72 + col] = acc[m][1];
            if (col + 8 < 72) {
                rp[(2 * t) * 72 + col + 8] = acc[m][2];
                rp[(2 * t + 1) * 72 + col + 8] = acc[m][3];
            }
        }
    }
    cons_sync();
    float4 o = make_float4(0.f, 0.f, 0.f, 0.f);
    if (tid < 144) {
        const float4 p0 = *(const float4*)(red + tid * 4), p1 = *(const float4*)(red + 576 + tid * 4);
        const float4 p2 = *(const float4*)(red + 1152 + tid * 4), p3 = *(const float4*)(red + 1728 + tid * 4);
        o.x = (p0.x + p1.x) + (p2.x + p3.x); o.y = (p0.y + p1.y) + (p2.y + p3.y);
        o.z = (p0.z + p1.z) + (p2.z + p3.z); o.w = (p0.w + p1.w) + (p2.w + p3.w);
    }
    return o;
}

__device__ __forceinline__ void send_slice(uint32_t w0, uint32_t w1, uint32_t buf, uint32_t bar, int rank, int tid) {
    const uint32_t n0 = __shfl_xor_sync(0xffffffffu, w0, 1), n1 = __shfl_xor_sync(0xffffffffu, w1, 1);
    if (tid < 144) {
        const int b = tid / 18, quad = tid - b * 18, odd = quad & 1;
        const uint4 v = odd ? make_uint4(n0, n1, w0, w1) : make_uint4(w0, w1, n0, n1);
        const uint32_t a = buf + (b * PITCH + rank * 72 + (quad & ~1) * 4) * 2;
#pragma unroll
        for (int d = 0; d < 4; d++) {
            const int dest = odd * 4 + d;
            st_async4(mapa(a, dest), v, mapa(bar, dest));
        }
    }
}

struct Params {
    const __nv_bfloat16* x;
    const __nv_bfloat16* k;
    const __nv_bfloat16* v;
    __nv_bfloat16* out;
};

__global__ void __cluster_dims__(CS, 1, 1) __launch_bounds__(288, 1)
fused_decode_kernel(const __grid_constant__ CUtensorMap map_wq, const __grid_constant__ CUtensorMap map_wo,
                    const __grid_constant__ CUtensorMap map_w1, const __grid_constant__ CUtensorMap map_w2,
                    const Params prm)
{
    extern __shared__ __align__(1024) unsigned char smem[];
    const uint32_t sb = smem_u32(smem);
    const int tid = threadIdx.x, warp = tid >> 5, lane = tid & 31;
    const int cl = blockIdx.x >> 3;
    const int r = blockIdx.x & 7;
    const uint32_t bars = sb + SM_BAR;
    auto BAR = [&](int i) -> uint32_t { return bars + i * 8; };

    if (warp == 8) {
        uint64_t pol = 0;
        const char* kv[2][2];
#pragma unroll
        for (int u = 0; u < 2; u++) {
            const size_t off = ((size_t)(r * HKV + 2 * cl + u) * SK + (SK - WIN)) * (DH * 2);
            kv[u][0] = (const char*)prm.k + off;
            kv[u][1] = (const char*)prm.v + off;
        }
        auto issue_fifo = [&](int i) {
            const int slot = item_slot(i);
            const uint32_t dst = sb + slot * SLOT, fb = BAR(BAR_FULL + slot);
            if (i < IT_KA) {
                mbar_expect_tx(fb, SLOT);
                tma_2d(dst, &map_wq, cl * 512 + r * 64, i * 128, fb, pol);
            } else if (i >= IT_WOA && i < IT_KB) {
                const int j = i - IT_WOA, nb = j < 2 ? 3 : 2;
                mbar_expect_tx(fb, nb * 32 * 144);
                for (int u = 0; u < nb; u++) tma_2d(dst + u * 32 * 144, &map_wo, r * 72, cl * 512 + j * 96 + u * 32, fb, pol);
            } else {
                const char* src = i < IT_VA ? kv[0][0] + (size_t)(i - IT_KA) * SLOT
                                : i < IT_WOA ? kv[0][1] + (size_t)(i - IT_VA) * SLOT
                                : i < IT_VB ? kv[1][0] + (size_t)(i - IT_KB) * SLOT
                                            : kv[1][1] + (size_t)(i - IT_VB) * SLOT;
                mbar_expect_tx(fb, SLOT);
                bulk_g2s(dst, src, SLOT, fb, pol);
            }
        };
        int i = 0;
        if (lane == 0) {
            DBG_T(0);
            for (int k = 0; k < NS; k++) { mbar_init(BAR(BAR_FULL + k), 1); mbar_init(BAR(BAR_EMPTY + k), 4); }
            for (int k = BAR_TW; k < BAR_WOFREE; k++) mbar_init(BAR(k), 1);
            mbar_init(BAR(BAR_WOFREE), 1);
            asm volatile("fence.mbarrier_init.release.cluster;" ::: "memory");
            asm volatile("fence.proxy.async.shared::cta;" ::: "memory");
            asm volatile("createpolicy.fractional.L2::evict_first.b64 %0, 1.0;" : "=l"(pol));
            for (; i < INFLIGHT; i++) issue_fifo(i);
            mbar_expect_tx(BAR(BAR_Q), CS * 128);
            mbar_expect_tx(BAR(BAR_OA), CS * 512);
            mbar_expect_tx(BAR(BAR_OB), CS * 512);
            mbar_expect_tx(BAR(BAR_H), CS * 1152);
            mbar_expect_tx(BAR(BAR_H1), CS * 1152);
        }
        __syncwarp();
        asm volatile("bar.sync 0;" ::: "memory");
        asm volatile("barrier.cluster.arrive.release.aligned;" ::: "memory");
        if (lane == 0) {
            for (; i < IT_FIFO_END; i++) {
                if (i >= NS) mbar_wait(BAR(BAR_EMPTY + i % NS), ((i / NS) - 1) & 1);
                mbar_wait(BAR(BAR_FULL + (i - INFLIGHT) % NS), ((i - INFLIGHT) / NS) & 1);
                issue_fifo(i);
            }
            auto issue_w1 = [&](int k) {
                mbar_expect_tx(BAR(BAR_TW + 3 + k), CHUNK);
                tma_2d(sb + TAIL_W1 + k * CHUNK, &map_w1, cl * 576 + r * 72, k * 96, BAR(BAR_TW + 3 + k), pol);
            };
            auto issue_wob = [&](int j) {
                const int nb = j < 2 ? 3 : 2;
                mbar_expect_tx(BAR(BAR_TW + j), nb * 32 * 144);
                for (int u = 0; u < nb; u++)
                    tma_2d(sb + TAIL + j * CHUNK + u * 32 * 144, &map_wo, r * 72, cl * 512 + 256 + j * 96 + u * 32, BAR(BAR_TW + j), pol);
            };
            auto issue_w2 = [&](int k, uint32_t dst) {
                mbar_expect_tx(BAR(BAR_TW + 9 + k), CHUNK);
                tma_2d(dst, &map_w2, r * 72, cl * 576 + k * 96, BAR(BAR_TW + 9 + k), pol);
            };
            mbar_wait(BAR(BAR_EMPTY + 8), 1); mbar_wait(BAR(BAR_EMPTY + 9), 1); issue_w1(3);
            mbar_wait(BAR(BAR_EMPTY + 10), 1); issue_w1(4);
            mbar_wait(BAR(BAR_EMPTY + 11), 1); issue_w1(5);
            for (int k = 0; k < 4; k++) { mbar_wait(BAR(BAR_EMPTY + k), 0); issue_fifo(IT_FIFO_END + k); }
            mbar_wait(BAR(BAR_EMPTY + 4), 0); issue_wob(0);
            mbar_wait(BAR(BAR_EMPTY + 5), 0); issue_wob(1);
            mbar_wait(BAR(BAR_EMPTY + 6), 0); issue_wob(2);
            mbar_wait(BAR(BAR_EMPTY + 7), 0); issue_w1(0); issue_w1(1); issue_w1(2);
            for (int k = 0; k < 4; k++) { mbar_wait(BAR(BAR_EMPTY + k), 1); issue_fifo(IT_FIFO_END + 4 + k); }
            for (int k = 0; k < 4; k++) { mbar_wait(BAR(BAR_EMPTY + k), 0); issue_w2(k, sb + k * SLOT); }
            mbar_wait(BAR(BAR_WOFREE), 0);
            issue_w2(4, sb + TAIL); issue_w2(5, sb + TAIL + CHUNK);
            DBG_T(1);
        }
        return;
    }

    const int g = lane >> 2, t = lane & 3;
    uint32_t xw[9];
    {
        const uint32_t* xr = (const uint32_t*)(prm.x + warp * DM);
#pragma unroll
        for (int j = 0; j < 9; j++) xw[j] = __ldg(xr + j * 32 + lane);
    }
    const int qb = tid / 18, qq = tid - qb * 18;
    uint2 xres = make_uint2(0, 0);
    if (tid < 144) {
        xres = __ldg((const uint2*)(prm.x + qb * DM + r * 72 + qq * 4));
        st_pub4(&g_scr.ap[r][cl][tid * 4], make_uint4(SENT, SENT, SENT, SENT));
        st_pub4(&g_scr.fp[r][cl][tid * 4], make_uint4(SENT, SENT, SENT, SENT));
    }
    layernorm_row(xw);
    {
        uint32_t* act = (uint32_t*)(smem + SM_R2) + warp * (PITCH / 2);
#pragma unroll
        for (int j = 0; j < 9; j++) act[j * 32 + lane] = xw[j];
    }
    asm volatile("bar.sync 0;" ::: "memory");
    asm volatile("barrier.cluster.arrive.release.aligned;" ::: "memory");
    if (tid == 0) {
        __threadfence();
        asm volatile("red.relaxed.gpu.global.add.u32 [%0], 1;" ::"l"(&g_cnt) : "memory");
    }
    DBG_T(2);

    {
        const int m = warp & 3, kh = warp >> 2;
#pragma unroll
        for (int j = 0; j < 5; j++) mbar_wait(BAR(BAR_FULL + j), 0);
        float ca[4] = {0.f, 0.f, 0.f, 0.f}, cb[4] = {0.f, 0.f, 0.f, 0.f};
        const int lrow = (lane & 7) + ((lane >> 4) & 1) * 8;
        const int lchunk = m * 2 + ((lane >> 3) & 1);
        const uint32_t baddr = sb + SM_R2 + (lane & 7) * (PITCH * 2) + (lane >> 3) * 16;
#pragma unroll
        for (int s = 0; s < 18; s += 2) {
            const int ks = kh * 18 + s;
            uint32_t a0, a1, a2, a3, b0, b1, b2, b3;
            ldsm_x4(b0, b1, b2, b3, baddr + ks * 32);
            {
                const int row = ks * 16 + lrow;
                ldsm_x4_t(a0, a1, a2, a3, sb + row * 128 + ((lchunk ^ (row & 7)) << 4));
                mma16816(ca, a0, a1, a2, a3, b0, b1);
            }
            {
                const int row = ks * 16 + 16 + lrow;
                ldsm_x4_t(a0, a1, a2, a3, sb + row * 128 + ((lchunk ^ (row & 7)) << 4));
                mma16816(cb, a0, a1, a2, a3, b2, b3);
            }
        }
        float* red = (float*)(smem + SM_R1);
        red[(kh * 8 + 2 * t) * 64 + m * 16 + g] = ca[0] + cb[0];
        red[(kh * 8 + 2 * t + 1) * 64 + m * 16 + g] = ca[1] + cb[1];
        red[(kh * 8 + 2 * t) * 64 + m * 16 + g + 8] = ca[2] + cb[2];
        red[(kh * 8 + 2 * t + 1) * 64 + m * 16 + g + 8] = ca[3] + cb[3];
        cons_sync();
        if (warp < 4 && lane == 0) {
#pragma unroll
            for (int j = 0; j < 5; j++) mbar_arrive(BAR(BAR_EMPTY + j));
        }
        asm volatile("barrier.cluster.wait.acquire.aligned;" ::: "memory");
        if (tid < 64) {
            const int b = tid >> 3, oct = tid & 7;
            const float* p0 = red + b * 64 + oct * 8;
            const float4 u0 = *(const float4*)p0, u1 = *(const float4*)(p0 + 4);
            const float4 v0 = *(const float4*)(p0 + 512), v1 = *(const float4*)(p0 + 516);
            const uint4 w = make_uint4(bf16_pack(u0.x + v0.x, u0.y + v0.y), bf16_pack(u0.z + v0.z, u0.w + v0.w),
                                       bf16_pack(u1.x + v1.x, u1.y + v1.y), bf16_pack(u1.z + v1.z, u1.w + v1.w));
            st_async4(mapa(sb + SM_QS + (r * 64 + oct * 8) * 2, b), w, mapa(BAR(BAR_Q), b));
        }
        mbar_wait_cl(BAR(BAR_Q));
        cons_sync();
    }
    DBG_T(3);

    float4 apart = make_float4(0.f, 0.f, 0.f, 0.f);

#pragma unroll 1
    for (int u = 0; u < 2; u++) {
        {
            uint32_t bq[16];
            {
                const int pi = (g >> 1) & 1, h = g & 1;
#pragma unroll
                for (int j = 0; j < 4; j++) {
                    uint4 v = lds128(sb + SM_QS + (u * 2 + h) * 256 + (4 * (j ^ pi) + t) * 16);
                    if (g >= 4) v = make_uint4(0, 0, 0, 0);
                    bq[4 * j] = v.x; bq[4 * j + 1] = v.y; bq[4 * j + 2] = v.z; bq[4 * j + 3] = v.w;
                }
            }
            const int pig = g & 1;
            const int first = (u ? IT_KB : IT_KA) + (warp >> 2);
            int slot = first % NS; uint32_t ph = (first / NS) & 1;
            const uint32_t rowoff = ((warp & 3) * 16 + g) * 256;
            unsigned short* sc = (unsigned short*)(smem + SM_R1);
            for (int kt = warp >> 2; kt < 32; kt += 2) {
                mbar_wait(BAR(BAR_FULL + slot), ph);
                const uint32_t base = sb + slot * SLOT + rowoff;
                uint4 X[4], Y[4];
#pragma unroll
                for (int j = 0; j < 4; j++) {
                    const uint32_t a = base + (4 * (j ^ pig) + t) * 16;
                    X[j] = lds128(a); Y[j] = lds128(a + 2048);
                }
                float ca[4] = {0.f, 0.f, 0.f, 0.f}, cb[4] = {0.f, 0.f, 0.f, 0.f};
#pragma unroll
                for (int j = 0; j < 4; j++) {
                    mma16816(ca, X[j].x, Y[j].x, X[j].y, Y[j].y, bq[4 * j], bq[4 * j + 1]);
                    mma16816(cb, X[j].z, Y[j].z, X[j].w, Y[j].w, bq[4 * j + 2], bq[4 * j + 3]);
                }
                __syncwarp();
                if (lane == 0) mbar_arrive(BAR(BAR_EMPTY + slot));
                if (t == pig) {
                    const int key = kt * 64 + (warp & 3) * 16 + g;
                    const float scale = 0.08838834764831845f;
                    sc[key] = (unsigned short)bf16_bits(bf16r(ca[0] + cb[0]) * scale);
                    sc[2048 + key] = (unsigned short)bf16_bits(bf16r(ca[1] + cb[1]) * scale);
                    sc[key + 8] = (unsigned short)bf16_bits(bf16r(ca[2] + cb[2]) * scale);
                    sc[2048 + key + 8] = (unsigned short)bf16_bits(bf16r(ca[3] + cb[3]) * scale);
                }
                slot += 2; if (slot >= NS) { slot -= NS; ph ^= 1; }
            }
        }
        cons_sync();
        if (u == 0) DBG_T(4); else DBG_T(7);

        {
            const int h = tid >> 7, idx = tid & 127;
            const uint32_t a = sb + SM_R1 + h * 4096 + idx * 32;
            const uint4 u0 = lds128(a), u1 = lds128(a + 16);
            float e[16];
            e[0] = bf_lo(u0.x); e[1] = bf_hi(u0.x); e[2] = bf_lo(u0.y); e[3] = bf_hi(u0.y);
            e[4] = bf_lo(u0.z); e[5] = bf_hi(u0.z); e[6] = bf_lo(u0.w); e[7] = bf_hi(u0.w);
            e[8] = bf_lo(u1.x); e[9] = bf_hi(u1.x); e[10] = bf_lo(u1.y); e[11] = bf_hi(u1.y);
            e[12] = bf_lo(u1.z); e[13] = bf_hi(u1.z); e[14] = bf_lo(u1.w); e[15] = bf_hi(u1.w);
            float mx = e[0];
#pragma unroll
            for (int i = 1; i < 16; i++) mx = fmaxf(mx, e[i]);
            mx = warp_max(mx);
            float* stat = (float*)(smem + SM_STAT);
            if (lane == 0) stat[warp] = mx;
            if (u == 1 && tid == 32) {
                uint32_t c, spins = 0;
                do {
                    asm volatile("ld.acquire.gpu.global.u32 %0, [%1];" : "=r"(c) : "l"(&g_cnt) : "memory");
                    if (++spins > (1u << 22)) __trap();
                } while (c < NCTA);
            }
            cons_sync();
            mx = fmaxf(fmaxf(stat[h * 4], stat[h * 4 + 1]), fmaxf(stat[h * 4 + 2], stat[h * 4 + 3]));
            float sum = 0.f;
#pragma unroll
            for (int i = 0; i < 16; i++) { e[i] = exp2f((e[i] - mx) * 1.4426950408889634f); sum += e[i]; }
            sum = warp_sum(sum);
            if (lane == 0) stat[8 + warp] = sum;
            cons_sync();
            sum = (stat[8 + h * 4] + stat[8 + h * 4 + 1]) + (stat[8 + h * 4 + 2] + stat[8 + h * 4 + 3]);
            const float inv = __fdiv_rn(1.0f, sum);
            uint32_t w[8];
#pragma unroll
            for (int i = 0; i < 8; i++) w[i] = bf16_pack(e[2 * i] * inv, e[2 * i + 1] * inv);
            *(uint4*)(smem + SM_R1 + h * 4096 + idx * 32) = make_uint4(w[0], w[1], w[2], w[3]);
            *(uint4*)(smem + SM_R1 + h * 4096 + idx * 32 + 16) = make_uint4(w[4], w[5], w[6], w[7]);
            cons_sync();
        }
        if (u == 0) DBG_T(5);

        {
            float acc[2][4][4];
#pragma unroll
            for (int a = 0; a < 2; a++)
#pragma unroll
                for (int b = 0; b < 4; b++)
#pragma unroll
                    for (int d = 0; d < 4; d++) acc[a][b][d] = 0.f;
            const int first = (u ? IT_VB : IT_VA) + (warp >> 2);
            const bool bvalid = (g >> 1) == t;
            const uint32_t paddr = sb + SM_R1 + (g & 1) * 4096 + ((warp & 3) * 16 + 4 * t) * 2;
            const uint32_t rowoff = ((warp & 3) * 16 + 4 * t) * 256 + (g ^ (2 * t)) * 16;
            for (int vt = warp >> 2; vt < 32; vt += 2) {
                const int item = first - (warp >> 2) + vt;
                const int slot = item_slot(item);
                const uint2 pbv = lds64(paddr + vt * 128);
                const uint32_t b0 = bvalid ? pbv.x : 0u, b1 = bvalid ? pbv.y : 0u;
                mbar_wait(BAR(BAR_FULL + slot), item_par(item));
                const uint32_t base = sb + slot * SLOT + rowoff;
                uint4 X[2][4];
#pragma unroll
                for (int hf = 0; hf < 2; hf++)
#pragma unroll
                    for (int i = 0; i < 4; i++) X[hf][i] = lds128(base + i * 256 + hf * 128);
#pragma unroll
                for (int hf = 0; hf < 2; hf++) {
                    const uint32_t x0[4] = {X[hf][0].x, X[hf][0].y, X[hf][0].z, X[hf][0].w};
                    const uint32_t x1[4] = {X[hf][1].x, X[hf][1].y, X[hf][1].z, X[hf][1].w};
                    const uint32_t x2[4] = {X[hf][2].x, X[hf][2].y, X[hf][2].z, X[hf][2].w};
                    const uint32_t x3[4] = {X[hf][3].x, X[hf][3].y, X[hf][3].z, X[hf][3].w};
#pragma unroll
                    for (int m = 0; m < 4; m++) {
                        mma16816(acc[hf][m], __byte_perm(x0[m], x1[m], 0x5410), __byte_perm(x0[m], x1[m], 0x7632),
                                 __byte_perm(x2[m], x3[m], 0x5410), __byte_perm(x2[m], x3[m], 0x7632), b0, b1);
                    }
                }
                __syncwarp();
                if (lane == 0) mbar_arrive(BAR(BAR_EMPTY + slot));
            }
            if (u == 0) DBG_T(6); else DBG_T(8);
            float k1[4][4];
            {
                const bool up = (t & 2) != 0;
#pragma unroll
                for (int m = 0; m < 4; m++)
#pragma unroll
                    for (int d = 0; d < 4; d++) {
                        const float keep = up ? acc[1][m][d] : acc[0][m][d];
                        const float send = up ? acc[0][m][d] : acc[1][m][d];
                        k1[m][d] = keep + __shfl_xor_sync(0xffffffffu, send, 18);
                    }
            }
            float k2[2][4];
            {
                const bool up = (t & 1) != 0;
#pragma unroll
                for (int m = 0; m < 2; m++)
#pragma unroll
                    for (int d = 0; d < 4; d++) {
                        const float keep = up ? k1[2 + m][d] : k1[m][d];
                        const float send = up ? k1[m][d] : k1[2 + m][d];
                        k2[m][d] = keep + __shfl_xor_sync(0xffffffffu, send, 9);
                    }
            }
            float* red = (float*)(smem + SM_R2);
            {
                const int d0 = ((g ^ (2 * t)) + 8 * (t >> 1)) * 8 + (t & 1) * 4;
                *(float4*)(red + warp * 256 + d0) = make_float4(k2[0][0], k2[0][2], k2[1][0], k2[1][2]);
                *(float4*)(red + warp * 256 + 128 + d0) = make_float4(k2[0][1], k2[0][3], k2[1][1], k2[1][3]);
            }
            cons_sync();
            float s = 0.f;
#pragma unroll
            for (int w = 0; w < 8; w++) s += red[w * 256 + tid];
            ((unsigned short*)(smem + SM_OL))[tid] = (unsigned short)bf16_bits(s);
            cons_sync();
            const uint4 ov = lds128(sb + SM_OL + lane * 16);
            const uint32_t obuf = sb + SM_R3 + u * (NB * OPITCH * 2);
            const uint32_t obar = BAR(u ? BAR_OB : BAR_OA);
            st_async4(mapa(obuf + r * (OPITCH * 2) + lane * 16, warp), ov, mapa(obar, warp));
            if (u == 0) {
#pragma unroll
                for (int j = 0; j < 3; j++) mbar_wait(BAR(BAR_FULL + (IT_WOA + j) % NS), ((IT_WOA + j) / NS) & 1);
            } else {
#pragma unroll
                for (int j = 0; j < 3; j++) mbar_wait(BAR(BAR_TW + j), 0);
            }
            mbar_wait_cl(obar);
            if (u == 1) DBG_T(9);
            const uint32_t wbase = u ? sb + TAIL : sb + (IT_WOA % NS) * SLOT;
            const uint32_t wstride = u ? CHUNK : SLOT;
            const float4 p = gemv72<16>(obuf, OPITCH, [&](int k) { return wbase + k * wstride; }, (float*)(smem + SM_R2), tid);
            apart.x += p.x; apart.y += p.y; apart.z += p.z; apart.w += p.w;
            if (u == 0) {
                if (warp < 4 && lane == 0) {
#pragma unroll
                    for (int j = 0; j < 3; j++) mbar_arrive(BAR(BAR_EMPTY + (IT_WOA + j) % NS));
                }
                cons_sync();
            } else {
                if (tid == 255) mbar_arrive(BAR(BAR_WOFREE));
            }
        }
    }

    uint32_t hw0 = 0, hw1 = 0;
    if (tid < 144) {
        st_pub4(&g_scr.ap[r][cl][tid * 4], make_uint4(f2pub(apart.x), f2pub(apart.y), f2pub(apart.z), f2pub(apart.w)));
        DBG_T(10);
        uint4 v[NCL];
        bool ok[NCL];
#pragma unroll
        for (int c = 0; c < NCL; c++) ok[c] = false;
        uint32_t spins = 0;
        while (true) {
#pragma unroll
            for (int c = 0; c < NCL; c++) if (!ok[c]) v[c] = ld_poll4(&g_scr.ap[r][c][tid * 4]);
            bool all = true;
#pragma unroll
            for (int c = 0; c < NCL; c++) { ok[c] = ok[c] || vec_valid(v[c]); all = all && ok[c]; }
            if (all) break;
            if (++spins > (1u << 22)) __trap();
        }
        float s0 = 0.f, s1 = 0.f, s2 = 0.f, s3 = 0.f;
#pragma unroll
        for (int c = 0; c < NCL; c++) {
            s0 += __uint_as_float(v[c].x); s1 += __uint_as_float(v[c].y);
            s2 += __uint_as_float(v[c].z); s3 += __uint_as_float(v[c].w);
        }
        const float h0 = bf16r(bf_lo(xres.x) + bf16r(s0)), h1 = bf16r(bf_hi(xres.x) + bf16r(s1));
        const float h2 = bf16r(bf_lo(xres.y) + bf16r(s2)), h3 = bf16r(bf_hi(xres.y) + bf16r(s3));
        hw0 = bf16_pack(h0, h1); hw1 = bf16_pack(h2, h3);
        if (qb == cl) *(float4*)(smem + SM_HS + qq * 16) = make_float4(h0, h1, h2, h3);
    }
    __syncwarp();
    if (warp < 5) send_slice(hw0, hw1, sb + SM_R1, BAR(BAR_H), r, tid);
    DBG_T(11);
    mbar_wait_cl(BAR(BAR_H));
    {
        uint32_t* row = (uint32_t*)(smem + SM_R1) + warp * (PITCH / 2);
        uint32_t w[9];
#pragma unroll
        for (int j = 0; j < 9; j++) w[j] = row[j * 32 + lane];
        layernorm_row(w);
#pragma unroll
        for (int j = 0; j < 9; j++) row[j * 32 + lane] = w[j];
    }
#pragma unroll
    for (int j = 0; j < 6; j++) mbar_wait(BAR(BAR_TW + 3 + j), 0);
    cons_sync();
    DBG_T(12);

    {
        const float4 p = gemv72<36>(sb + SM_R1, PITCH, [&](int k) { return sb + TAIL_W1 + k * CHUNK; }, (float*)(smem + SM_R2), tid);
        float a = bf16r(p.x), b = bf16r(p.y), c = bf16r(p.z), d = bf16r(p.w);
        a = (a != a) ? a : fmaxf(a, 0.f); b = (b != b) ? b : fmaxf(b, 0.f);
        c = (c != c) ? c : fmaxf(c, 0.f); d = (d != d) ? d : fmaxf(d, 0.f);
        __syncwarp();
        if (warp < 5) send_slice(bf16_pack(a, b), bf16_pack(c, d), sb + SM_R3, BAR(BAR_H1), r, tid);
    }
#pragma unroll
    for (int j = 0; j < 6; j++) mbar_wait(BAR(BAR_TW + 9 + j), 0);
    mbar_wait_cl(BAR(BAR_H1));
    cons_sync();
    DBG_T(13);

    {
        const float4 p = gemv72<36>(sb + SM_R3, PITCH,
                                    [&](int k) { return k < 4 ? sb + k * SLOT : sb + TAIL + (k - 4) * CHUNK; },
                                    (float*)(smem + SM_R2), tid);
        if (tid < 144) {
            st_pub4(&g_scr.fp[r][cl][tid * 4], make_uint4(f2pub(p.x), f2pub(p.y), f2pub(p.z), f2pub(p.w)));
            DBG_T(14);
            const int quad = tid >> 3, c = tid & 7;
            uint4 w;
            uint32_t spins = 0;
            while (true) {
                w = ld_poll4(&g_scr.fp[r][c][cl * 72 + quad * 4]);
                if (vec_valid(w)) break;
                if (++spins > (1u << 22)) __trap();
            }
            apart = make_float4(__uint_as_float(w.x), __uint_as_float(w.y), __uint_as_float(w.z), __uint_as_float(w.w));
        } else {
            apart = make_float4(0.f, 0.f, 0.f, 0.f);
        }
        if (warp < 5) {
            __syncwarp();
#pragma unroll
            for (int o = 1; o < 8; o <<= 1) {
                apart.x += __shfl_xor_sync(0xffffffffu, apart.x, o); apart.y += __shfl_xor_sync(0xffffffffu, apart.y, o);
                apart.z += __shfl_xor_sync(0xffffffffu, apart.z, o); apart.w += __shfl_xor_sync(0xffffffffu, apart.w, o);
            }
            if (tid < 144 && (tid & 7) == 0) {
                const int quad = tid >> 3;
                const float4 h = *(const float4*)(smem + SM_HS + quad * 16);
                uint2 o;
                o.x = bf16_pack(h.x + bf16r(apart.x), h.y + bf16r(apart.y));
                o.y = bf16_pack(h.z + bf16r(apart.z), h.w + bf16r(apart.w));
                *(uint2*)(prm.out + cl * DM + r * 72 + quad * 4) = o;
            }
            if (blockIdx.x == 0 && tid == 0) g_cnt = 0;
            DBG_T(15);
        }
    }
}

typedef CUresult (*EncodeTiledFn)(CUtensorMap*, CUtensorMapDataType, cuuint32_t, void*, const cuuint64_t*, const cuuint64_t*,
                                  const cuuint32_t*, const cuuint32_t*, CUtensorMapInterleave, CUtensorMapSwizzle,
                                  CUtensorMapL2promotion, CUtensorMapFloatOOBfill);

void make_map(EncodeTiledFn fn, CUtensorMap* m, const void* ptr, uint64_t cols, uint64_t rows, uint32_t bc, uint32_t br,
              CUtensorMapSwizzle sw) {
    cuuint64_t dims[2] = {cols, rows};
    cuuint64_t strides[1] = {cols * 2};
    cuuint32_t box[2] = {bc, br};
    cuuint32_t es[2] = {1, 1};
    fn(m, CU_TENSOR_MAP_DATA_TYPE_BFLOAT16, 2, const_cast<void*>(ptr), dims, strides, box, es, CU_TENSOR_MAP_INTERLEAVE_NONE, sw,
       CU_TENSOR_MAP_L2_PROMOTION_L2_256B, CU_TENSOR_MAP_FLOAT_OOB_FILL_NONE);
}

}

extern "C" void kernel_launch(void* const* d_in, const int* in_sizes, int n_in, void* d_out, int out_size) {
    (void)in_sizes; (void)n_in; (void)out_size;
    static EncodeTiledFn enc = nullptr;
    if (!enc) {
        void* fn = nullptr;
        cudaDriverEntryPointQueryResult qr;
        cudaGetDriverEntryPoint("cuTensorMapEncodeTiled", &fn, cudaEnableDefault, &qr);
        enc = (EncodeTiledFn)fn;
        cudaFuncSetAttribute(fused_decode_kernel, cudaFuncAttributeMaxDynamicSharedMemorySize, SM_TOTAL);
    }
    CUtensorMap mq, mo, m1, m2;
    make_map(enc, &mq, d_in[3], 4096, DM, 64, 128, CU_TENSOR_MAP_SWIZZLE_128B);
    make_map(enc, &mo, d_in[4], DM, 4096, 72, 32, CU_TENSOR_MAP_SWIZZLE_NONE);
    make_map(enc, &m1, d_in[6], DFF, DM, 72, 96, CU_TENSOR_MAP_SWIZZLE_NONE);
    make_map(enc, &m2, d_in[7], DM, DFF, 72, 96, CU_TENSOR_MAP_SWIZZLE_NONE);
    Params p;
    p.x = (const __nv_bfloat16*)d_in[0];
    p.k = (const __nv_bfloat16*)d_in[1];
    p.v = (const __nv_bfloat16*)d_in[2];
    p.out = (__nv_bfloat16*)d_out;
    fused_decode_kernel<<<NCTA, 288, SM_TOTAL, cudaStreamPerThread>>>(mq, mo, m1, m2, p);
}
```

```cpp
#include <cuda_runtime.h>
#include <cuda_bf16.h>
#include <cuda.h>
#include <stdint.h>

namespace {

constexpr int NB = 8;
constexpr int DM = 576;
constexpr int HKV = 16;
constexpr int DH = 128;
constexpr int SK = 8192;
constexpr int WIN = 2048;
constexpr int DFF = 4608;
constexpr int NCL = 8;
constexpr int CS = 8;
constexpr int NCTA = NCL * CS;

constexpr int SLOT = 16384;
constexpr int NS = 12;
constexpr int IT_KA = 5, IT_VA = 37, IT_WOA = 69, IT_KB = 72, IT_VB = 104, IT_FIFO_END = 128;
constexpr int CHUNK = 96 * 144;
constexpr int TAIL = 4 * SLOT;
constexpr int TAIL_W1 = TAIL + 256 * 144;

#define POLL_DELAY 300
#define TRIG_TILE 12
#define W2_TRIG 3
#define WOFREE_EARLY 0
#define W1_LATE 6
#define W1_WAIT_SLOT 3
#define INFLIGHT 8

constexpr int PITCH = 584;
constexpr int OPITCH = 264;
constexpr int SM_R1 = NS * SLOT;
constexpr int SM_R2 = SM_R1 + NB * PITCH * 2;
constexpr int SM_R3 = SM_R2 + NB * PITCH * 2;
constexpr int SM_QS = SM_R3 + NB * PITCH * 2;
constexpr int SM_HS = SM_QS + 1024;
constexpr int SM_OL = SM_HS + 288;
constexpr int SM_STAT = SM_OL + 512;
constexpr int SM_BAR = SM_STAT + 64;
constexpr int BAR_FULL = 0, BAR_EMPTY = 12, BAR_TW = 24, BAR_Q = 39, BAR_OA = 40, BAR_OB = 41, BAR_H = 42, BAR_H1 = 43,
              BAR_WOFREE = 44, BAR_TRIG = 45, BAR_RSTOK = 46, BAR_W2GO = 47, NBAR = 48;
constexpr int SM_DBG = SM_BAR + NBAR * 8;
constexpr int SM_TOTAL = SM_DBG + 32 * 8;
static_assert(SM_TOTAL <= 232448, "smem");
static_assert(2 * NB * OPITCH * 2 <= NB * PITCH * 2, "o_all");

constexpr uint32_t SENT = 0xffffffffu;

struct Scratch {
    uint32_t ap[CS][NCL][576];
    uint32_t fp[CS][NCL][576];
};
__device__ __align__(128) Scratch g_scr;
__device__ uint32_t g_cnt;

#define DBG_T(i) do { } while (0)

__device__ __forceinline__ uint32_t smem_u32(const void* p) { return (uint32_t)__cvta_generic_to_shared(p); }
__device__ __forceinline__ unsigned long long gtime() {
    unsigned long long t; asm volatile("mov.u64 %0, %globaltimer;" : "=l"(t)); return t;
}
__device__ __forceinline__ void mbar_init(uint32_t bar, uint32_t cnt) {
    asm volatile("mbarrier.init.shared::cta.b64 [%0], %1;" ::"r"(bar), "r"(cnt) : "memory");
}
__device__ __forceinline__ void mbar_expect_tx(uint32_t bar, uint32_t bytes) {
    asm volatile("mbarrier.arrive.expect_tx.shared::cta.b64 _, [%0], %1;" ::"r"(bar), "r"(bytes) : "memory");
}
__device__ __forceinline__ void mbar_arrive(uint32_t bar) {
    asm volatile("mbarrier.arrive.shared::cta.b64 _, [%0];" ::"r"(bar) : "memory");
}
__device__ __forceinline__ bool mbar_try(uint32_t bar, uint32_t parity) {
    uint32_t ok;
    asm volatile("{\n.reg .pred p;\nmbarrier.try_wait.parity.shared::cta.b64 p, [%1], %2;\nselp.u32 %0, 1, 0, p;\n}"
                 : "=r"(ok) : "r"(bar), "r"(parity) : "memory");
    return ok != 0;
}
__device__ __forceinline__ void mbar_wait(uint32_t bar, uint32_t parity) {
    uint32_t spins = 0;
    while (!mbar_try(bar, parity)) {
        if (++spins > (1u << 22)) __trap();
    }
}
__device__ __forceinline__ bool mbar_try_cl(uint32_t bar, uint32_t parity) {
    uint32_t ok;
    asm volatile("{\n.reg .pred p;\nmbarrier.try_wait.parity.acquire.cluster.shared::cta.b64 p, [%1], %2;\nselp.u32 %0, 1, 0, p;\n}"
                 : "=r"(ok) : "r"(bar), "r"(parity) : "memory");
    return ok != 0;
}
__device__ __forceinline__ void mbar_wait_cl(uint32_t bar) {
    uint32_t spins = 0;
    while (!mbar_try_cl(bar, 0)) {
        if (++spins > (1u << 22)) __trap();
    }
}
__device__ __forceinline__ void bulk_g2s(uint32_t dst, const void* src, uint32_t bytes, uint32_t bar, uint64_t pol) {
    asm volatile("cp.async.bulk.shared::cluster.global.mbarrier::complete_tx::bytes.L2::cache_hint [%0], [%1], %2, [%3], %4;"
                 ::"r"(dst), "l"(src), "r"(bytes), "r"(bar), "l"(pol) : "memory");
}
__device__ __forceinline__ void tma_2d(uint32_t dst, const CUtensorMap* map, int x, int y, uint32_t bar, uint64_t pol) {
    asm volatile("cp.async.bulk.tensor.2d.shared::cluster.global.mbarrier::complete_tx::bytes.L2::cache_hint [%0], [%1, {%3, %4}], [%2], %5;"
                 ::"r"(dst), "l"(map), "r"(bar), "r"(x), "r"(y), "l"(pol) : "memory");
}
__device__ __forceinline__ void cons_sync() { asm volatile("bar.sync 1, 256;" ::: "memory"); }
__device__ __forceinline__ uint32_t mapa(uint32_t a, uint32_t rank) {
    uint32_t r; asm("mapa.shared::cluster.u32 %0, %1, %2;" : "=r"(r) : "r"(a), "r"(rank)); return r;
}
__device__ __forceinline__ void st_async4(uint32_t addr, uint4 v, uint32_t bar) {
    asm volatile("st.async.weak.shared::cluster.mbarrier::complete_tx::bytes.v4.b32 [%0], {%1,%2,%3,%4}, [%5];"
                 ::"r"(addr), "r"(v.x), "r"(v.y), "r"(v.z), "r"(v.w), "r"(bar) : "memory");
}
__device__ __forceinline__ uint4 lds128(uint32_t a) {
    uint4 v; asm volatile("ld.shared.v4.u32 {%0,%1,%2,%3}, [%4];" : "=r"(v.x), "=r"(v.y), "=r"(v.z), "=r"(v.w) : "r"(a)); return v;
}
__device__ __forceinline__ uint2 lds64(uint32_t a) {
    uint2 v; asm volatile("ld.shared.v2.u32 {%0,%1}, [%2];" : "=r"(v.x), "=r"(v.y) : "r"(a)); return v;
}
__device__ __forceinline__ void ldsm_x4(uint32_t& r0, uint32_t& r1, uint32_t& r2, uint32_t& r3, uint32_t a) {
    asm volatile("ldmatrix.sync.aligned.m8n8.x4.shared.b16 {%0,%1,%2,%3}, [%4];"
                 : "=r"(r0), "=r"(r1), "=r"(r2), "=r"(r3) : "r"(a));
}
__device__ __forceinline__ void ldsm_x2(uint32_t& r0, uint32_t& r1, uint32_t a) {
    asm volatile("ldmatrix.sync.aligned.m8n8.x2.shared.b16 {%0,%1}, [%2];" : "=r"(r0), "=r"(r1) : "r"(a));
}
__device__ __forceinline__ void ldsm_x4_t(uint32_t& r0, uint32_t& r1, uint32_t& r2, uint32_t& r3, uint32_t a) {
    asm volatile("ldmatrix.sync.aligned.m8n8.x4.trans.shared.b16 {%0,%1,%2,%3}, [%4];"
                 : "=r"(r0), "=r"(r1), "=r"(r2), "=r"(r3) : "r"(a));
}
__device__ __forceinline__ void mma16816(float (&c)[4], uint32_t a0, uint32_t a1, uint32_t a2, uint32_t a3, uint32_t b0, uint32_t b1) {
    asm volatile("mma.sync.aligned.m16n8k16.row.col.f32.bf16.bf16.f32 {%0,%1,%2,%3}, {%4,%5,%6,%7}, {%8,%9}, {%0,%1,%2,%3};"
                 : "+f"(c[0]), "+f"(c[1]), "+f"(c[2]), "+f"(c[3])
                 : "r"(a0), "r"(a1), "r"(a2), "r"(a3), "r"(b0), "r"(b1));
}
__device__ __forceinline__ uint4 ld_poll4(const uint32_t* p) {
    uint4 v;
    asm volatile("ld.relaxed.gpu.global.v4.u32 {%0,%1,%2,%3}, [%4];" : "=r"(v.x), "=r"(v.y), "=r"(v.z), "=r"(v.w) : "l"(p) : "memory");
    return v;
}
__device__ __forceinline__ void st_pub4(uint32_t* p, uint4 v) {
    asm volatile("st.relaxed.gpu.global.v4.u32 [%0], {%1,%2,%3,%4};" ::"l"(p), "r"(v.x), "r"(v.y), "r"(v.z), "r"(v.w) : "memory");
}
__device__ __forceinline__ bool vec_valid(const uint4& v) { return v.x != SENT && v.y != SENT && v.z != SENT && v.w != SENT; }
__device__ __forceinline__ uint32_t f2pub(float f) { uint32_t u = __float_as_uint(f); return u == SENT ? 0x7fffffffu : u; }

__device__ __forceinline__ uint32_t bf16_pack(float lo, float hi) {
    uint32_t r; asm("cvt.rn.bf16x2.f32 %0, %1, %2;" : "=r"(r) : "f"(hi), "f"(lo)); return r;
}
__device__ __forceinline__ uint32_t bf16_bits(float f) { return bf16_pack(f, 0.f); }
__device__ __forceinline__ float bf16r(float f) { return __uint_as_float(bf16_pack(0.f, f)); }
__device__ __forceinline__ float bf_lo(uint32_t w) { return __uint_as_float(w << 16); }
__device__ __forceinline__ float bf_hi(uint32_t w) { return __uint_as_float(w & 0xffff0000u); }
__device__ __forceinline__ float warp_sum(float v) {
#pragma unroll
    for (int o = 16; o > 0; o >>= 1) v += __shfl_xor_sync(0xffffffffu, v, o);
    return v;
}
__device__ __forceinline__ float warp_max(float v) {
#pragma unroll
    for (int o = 16; o > 0; o >>= 1) v = fmaxf(v, __shfl_xor_sync(0xffffffffu, v, o));
    return v;
}

__device__ __forceinline__ void layernorm_row(uint32_t (&w)[9]) {
    float v[18];
#pragma unroll
    for (int j = 0; j < 9; j++) { v[2 * j] = bf_lo(w[j]); v[2 * j + 1] = bf_hi(w[j]); }
    const float x0 = __shfl_sync(0xffffffffu, v[0], 0);
    float s0 = 0.f, s1 = 0.f, s2 = 0.f, q0 = 0.f, q1 = 0.f, q2 = 0.f;
#pragma unroll
    for (int i = 0; i < 6; i++) {
        const float d0 = v[i] - x0, d1 = v[6 + i] - x0, d2 = v[12 + i] - x0;
        s0 += d0; s1 += d1; s2 += d2;
        q0 += d0 * d0; q1 += d1 * d1; q2 += d2 * d2;
    }
    float s = (s0 + s1) + s2, q = (q0 + q1) + q2;
#pragma unroll
    for (int o = 16; o > 0; o >>= 1) { s += __shfl_xor_sync(0xffffffffu, s, o); q += __shfl_xor_sync(0xffffffffu, q, o); }
    const float md = s * (1.0f / 576.0f);
    const float m_b = bf16r(x0 + md);
    const float var_b = bf16r(fmaxf(q * (1.0f / 576.0f) - md * md, 0.f));
    const float sd = bf16r(__fsqrt_rn(bf16r(var_b + 1e-5f)));
    const float inv = __frcp_rn(sd);
#pragma unroll
    for (int j = 0; j < 9; j++)
        w[j] = bf16_pack(bf16r(v[2 * j] - m_b) * inv, bf16r(v[2 * j + 1] - m_b) * inv);
}

__device__ __forceinline__ int item_slot(int i) { return i < IT_FIFO_END ? i % NS : (i - IT_FIFO_END) & 3; }
__device__ __forceinline__ uint32_t item_par(int i) { return i < IT_FIFO_END ? (i / NS) & 1 : (i < IT_FIFO_END + 4 ? 1u : 0u); }

template <int KQ, typename ChunkAddr>
__device__ __forceinline__ void gemv_load(uint32_t (&af)[KQ][3][4], ChunkAddr chunk_addr, int tid) {
    const int warp = tid >> 5, lane = tid & 31;
    const int kq = warp & 3, mg = warp >> 2;
    const int lrow = (lane & 7) + ((lane >> 4) & 1) * 8;
    const int lcol = ((lane >> 3) & 1) * 16;
#pragma unroll
    for (int s = 0; s < KQ; s++) {
        const int ks = kq * KQ + s;
        const uint32_t a = chunk_addr(ks / 6) + ((ks % 6) * 16 + lrow) * 144 + lcol + mg * 96;
        ldsm_x4_t(af[s][0][0], af[s][0][1], af[s][0][2], af[s][0][3], a);
        ldsm_x4_t(af[s][1][0], af[s][1][1], af[s][1][2], af[s][1][3], a + 32);
        if (mg == 0) ldsm_x4_t(af[s][2][0], af[s][2][1], af[s][2][2], af[s][2][3], a + 64);
        else { af[s][2][0] = af[s][2][1] = af[s][2][2] = af[s][2][3] = 0; }
    }
}
template <int KQ>
__device__ __forceinline__ float4 gemv_mma(const uint32_t (&af)[KQ][3][4], uint32_t act, int apitch, float* red, int tid) {
    const int warp = tid >> 5, lane = tid & 31, g = lane >> 2, t = lane & 3;
    const int kq = warp & 3, mg = warp >> 2;
    float acc[3][4], acd[3][4];
#pragma unroll
    for (int m = 0; m < 3; m++) {
        acc[m][0] = acc[m][1] = acc[m][2] = acc[m][3] = 0.f;
        acd[m][0] = acd[m][1] = acd[m][2] = acd[m][3] = 0.f;
    }
    const uint32_t baddr = act + (lane & 7) * (apitch * 2) + (lane >> 3) * 16 + kq * KQ * 32;
    uint32_t bf[KQ + 1][2];
#pragma unroll
    for (int s = 0; s + 1 < KQ; s += 2) ldsm_x4(bf[s][0], bf[s][1], bf[s + 1][0], bf[s + 1][1], baddr + s * 32);
    if (KQ & 1) ldsm_x2(bf[KQ - 1][0], bf[KQ - 1][1], act + (lane & 7) * (apitch * 2) + ((lane >> 3) & 1) * 16 + (kq * KQ + KQ - 1) * 32);
#pragma unroll
    for (int s = 0; s < KQ; s++) {
        if (s & 1) {
            mma16816(acd[0], af[s][0][0], af[s][0][1], af[s][0][2], af[s][0][3], bf[s][0], bf[s][1]);
            mma16816(acd[1], af[s][1][0], af[s][1][1], af[s][1][2], af[s][1][3], bf[s][0], bf[s][1]);
            if (mg == 0) mma16816(acd[2], af[s][2][0], af[s][2][1], af[s][2][2], af[s][2][3], bf[s][0], bf[s][1]);
        } else {
            mma16816(acc[0], af[s][0][0], af[s][0][1], af[s][0][2], af[s][0][3], bf[s][0], bf[s][1]);
            mma16816(acc[1], af[s][1][0], af[s][1][1], af[s][1][2], af[s][1][3], bf[s][0], bf[s][1]);
            if (mg == 0) mma16816(acc[2], af[s][2][0], af[s][2][1], af[s][2][2], af[s][2][3], bf[s][0], bf[s][1]);
        }
    }
    float* rp = red + kq * 576;
#pragma unroll
    for (int m = 0; m < 3; m++) {
        const int col = mg * 48 + m * 16 + g;
        if (m < 2 || mg == 0) {
            rp[(2 * t) * 72 + col] = acc[m][0] + acd[m][0];
            rp[(2 * t + 1) * 72 + col] = acc[m][1] + acd[m][1];
            if (col + 8 < 72) {
                rp[(2 * t) * 72 + col + 8] = acc[m][2] + acd[m][2];
                rp[(2 * t + 1) * 72 + col + 8] = acc[m][3] + acd[m][3];
            }
        }
    }
    cons_sync();
    float4 o = make_float4(0.f, 0.f, 0.f, 0.f);
    if (tid < 144) {
        const float4 p0 = *(const float4*)(red + tid * 4), p1 = *(const float4*)(red + 576 + tid * 4);
        const float4 p2 = *(const float4*)(red + 1152 + tid * 4), p3 = *(const float4*)(red + 1728 + tid * 4);
        o.x = (p0.x + p1.x) + (p2.x + p3.x); o.y = (p0.y + p1.y) + (p2.y + p3.y);
        o.z = (p0.z + p1.z) + (p2.z + p3.z); o.w = (p0.w + p1.w) + (p2.w + p3.w);
    }
    return o;
}

__device__ __forceinline__ void send_slice(uint32_t w0, uint32_t w1, uint32_t buf, uint32_t bar, int rank, int tid) {
    const uint32_t n0 = __shfl_xor_sync(0xffffffffu, w0, 1), n1 = __shfl_xor_sync(0xffffffffu, w1, 1);
    if (tid < 144) {
        const int b = tid / 18, quad = tid - b * 18, odd = quad & 1;
        const uint4 v = odd ? make_uint4(n0, n1, w0, w1) : make_uint4(w0, w1, n0, n1);
        const uint32_t a = buf + (b * PITCH + rank * 72 + (quad & ~1) * 4) * 2;
#pragma unroll
        for (int d = 0; d < 4; d++) {
            const int dest = odd * 4 + d;
            st_async4(mapa(a, dest), v, mapa(bar, dest));
        }
    }
}

struct Params {
    const __nv_bfloat16* x;
    const __nv_bfloat16* k;
    const __nv_bfloat16* v;
    __nv_bfloat16* out;
};

__global__ void __cluster_dims__(CS, 1, 1) __launch_bounds__(320, 1)
fused_decode_kernel(const __grid_constant__ CUtensorMap map_wq, const __grid_constant__ CUtensorMap map_wo,
                    const __grid_constant__ CUtensorMap map_w1, const __grid_constant__ CUtensorMap map_w2,
                    const Params prm)
{
    extern __shared__ __align__(1024) unsigned char smem[];
    const uint32_t sb = smem_u32(smem);
    const int tid = threadIdx.x, warp = tid >> 5, lane = tid & 31;
    const int cl = blockIdx.x >> 3;
    const int r = blockIdx.x & 7;
    const uint32_t bars = sb + SM_BAR;
    auto BAR = [&](int i) -> uint32_t { return bars + i * 8; };

    constexpr uint64_t pol = 0x12F0000000000000ull;
    int tid_op;
    asm volatile("mov.u32 %0, %1;" : "=r"(tid_op) : "r"(tid));
    if (tid_op == 256) {
        DBG_T(0);
#pragma unroll
        for (int k = 0; k < INFLIGHT; k++) mbar_init(BAR(BAR_FULL + k), 1);
        asm volatile("fence.mbarrier_init.release.cluster;" ::: "memory");
        const char* k0 = (const char*)prm.k + ((size_t)(r * HKV + 2 * cl) * SK + (SK - WIN)) * (DH * 2);
#pragma unroll
        for (int k = IT_KA; k < INFLIGHT; k++) {
            mbar_expect_tx(BAR(BAR_FULL + k), SLOT);
            bulk_g2s(sb + k * SLOT, k0 + (size_t)(k - IT_KA) * SLOT, SLOT, BAR(BAR_FULL + k), pol);
        }
#pragma unroll
        for (int k = 0; k < IT_KA; k++) {
            mbar_expect_tx(BAR(BAR_FULL + k), SLOT);
            tma_2d(sb + k * SLOT, &map_wq, cl * 512 + r * 64, k * 128, BAR(BAR_FULL + k), pol);
        }
        DBG_T(16);
    } else if (tid_op == 288) {
#pragma unroll 1
        for (int k = BAR_FULL + INFLIGHT; k < NBAR; k++) mbar_init(BAR(k), (k >= BAR_EMPTY && k < BAR_TW) ? 4 : 1);
        mbar_expect_tx(BAR(BAR_Q), CS * 128);
        mbar_expect_tx(BAR(BAR_OA), CS * 512);
        mbar_expect_tx(BAR(BAR_OB), CS * 512);
        mbar_expect_tx(BAR(BAR_H), CS * 1152);
        mbar_expect_tx(BAR(BAR_H1), CS * 1152);
        asm volatile("fence.mbarrier_init.release.cluster;" ::: "memory");
    }
    __syncwarp();
    if (warp == 8) {
        const char* kv[2][2];
#pragma unroll
        for (int u = 0; u < 2; u++) {
            const size_t off = ((size_t)(r * HKV + 2 * cl + u) * SK + (SK - WIN)) * (DH * 2);
            kv[u][0] = (const char*)prm.k + off;
            kv[u][1] = (const char*)prm.v + off;
        }
        auto issue_fifo = [&](int i) {
            const int slot = item_slot(i);
            const uint32_t dst = sb + slot * SLOT, fb = BAR(BAR_FULL + slot);
            if (i < IT_KA) {
                mbar_expect_tx(fb, SLOT);
                tma_2d(dst, &map_wq, cl * 512 + r * 64, i * 128, fb, pol);
            } else if (i >= IT_WOA && i < IT_KB) {
                const int j = i - IT_WOA, nb = j < 2 ? 3 : 2;
                mbar_expect_tx(fb, nb * 32 * 144);
                for (int u = 0; u < nb; u++) tma_2d(dst + u * 32 * 144, &map_wo, r * 72, cl * 512 + j * 96 + u * 32, fb, pol);
            } else {
                const char* src = i < IT_VA ? kv[0][0] + (size_t)(i - IT_KA) * SLOT
                                : i < IT_WOA ? kv[0][1] + (size_t)(i - IT_VA) * SLOT
                                : i < IT_VB ? kv[1][0] + (size_t)(i - IT_KB) * SLOT
                                            : kv[1][1] + (size_t)(i - IT_VB) * SLOT;
                mbar_expect_tx(fb, SLOT);
                bulk_g2s(dst, src, SLOT, fb, pol);
            }
        };
        int i = INFLIGHT;
        asm volatile("bar.sync 0, 320;" ::: "memory");
        asm volatile("barrier.cluster.arrive.relaxed.aligned;" ::: "memory");
        if (lane == 0) {
            for (; i < IT_FIFO_END; i++) {
                if (i >= NS) mbar_wait(BAR(BAR_EMPTY + i % NS), ((i / NS) - 1) & 1);
                mbar_wait(BAR(BAR_FULL + (i - INFLIGHT) % NS), ((i - INFLIGHT) / NS) & 1);
                issue_fifo(i);
            }
            auto issue_w1 = [&](int k) {
                mbar_expect_tx(BAR(BAR_TW + 3 + k), CHUNK);
                tma_2d(sb + TAIL_W1 + k * CHUNK, &map_w1, cl * 576 + r * 72, k * 96, BAR(BAR_TW + 3 + k), pol);
            };
            auto issue_wob = [&](int j) {
                const int nb = j < 2 ? 3 : 2;
                mbar_expect_tx(BAR(BAR_TW + j), nb * 32 * 144);
                for (int u = 0; u < nb; u++)
                    tma_2d(sb + TAIL + j * CHUNK + u * 32 * 144, &map_wo, r * 72, cl * 512 + 256 + j * 96 + u * 32, BAR(BAR_TW + j), pol);
            };
            auto issue_w2 = [&](int k, uint32_t dst) {
                mbar_expect_tx(BAR(BAR_TW + 9 + k), CHUNK);
                tma_2d(dst, &map_w2, r * 72, cl * 576 + k * 96, BAR(BAR_TW + 9 + k), pol);
            };
            mbar_wait(BAR(BAR_EMPTY + 8), 1); mbar_wait(BAR(BAR_EMPTY + 9), 1);
            mbar_wait(BAR(BAR_EMPTY + 10), 1); mbar_wait(BAR(BAR_EMPTY + 11), 1);
            for (int k = 5; k >= 3; k--) if (k >= W1_LATE) issue_w1(k);
            for (int k = 0; k < 4; k++) { mbar_wait(BAR(BAR_EMPTY + k), 0); issue_fifo(IT_FIFO_END + k); }
            mbar_wait(BAR(BAR_EMPTY + 4), 0); issue_wob(0);
            mbar_wait(BAR(BAR_EMPTY + 5), 0); issue_wob(1);
            mbar_wait(BAR(BAR_EMPTY + 6), 0); issue_wob(2);
            mbar_wait(BAR(BAR_EMPTY + 7), 0);
            for (int k = 2; k >= 0; k--) if (k >= W1_LATE) issue_w1(k);
            for (int k = 0; k < 4; k++) { mbar_wait(BAR(BAR_EMPTY + k), 1); issue_fifo(IT_FIFO_END + 4 + k); }
            mbar_wait(BAR(BAR_FULL + W1_WAIT_SLOT), 0);
            for (int k = 0; k < W1_LATE; k++) issue_w1(k);
            mbar_wait(BAR(BAR_W2GO), 0);
            for (int k = 0; k < 4; k++) { mbar_wait(BAR(BAR_EMPTY + k), 0); issue_w2(k, sb + k * SLOT); }
            mbar_wait(BAR(BAR_WOFREE), 0);
            issue_w2(4, sb + TAIL); issue_w2(5, sb + TAIL + CHUNK);
            DBG_T(1);
        }
        return;
    }

    if (warp == 9) {
        asm volatile("bar.arrive 0, 320;" ::: "memory");
        asm volatile("barrier.cluster.arrive.relaxed.aligned;" ::: "memory");
        if (lane >= 1 && lane < 4) {
            const CUtensorMap* mp = lane == 1 ? &map_wo : lane == 2 ? &map_w1 : &map_w2;
            asm volatile("prefetch.tensormap [%0];" ::"l"(mp) : "memory");
        }
        mbar_wait(BAR(BAR_TRIG), 0);
        for (int i = lane; i < 144; i += 32) {
            st_pub4(&g_scr.ap[r][cl][i * 4], make_uint4(SENT, SENT, SENT, SENT));
            st_pub4(&g_scr.fp[r][cl][i * 4], make_uint4(SENT, SENT, SENT, SENT));
        }
        __threadfence();
        __syncwarp();
        if (lane == 0) {
            __threadfence();
            asm volatile("red.relaxed.gpu.global.add.u32 [%0], 1;" ::"l"(&g_cnt) : "memory");
            uint32_t c, spins = 0;
            do {
                asm volatile("ld.acquire.gpu.global.u32 %0, [%1];" : "=r"(c) : "l"(&g_cnt) : "memory");
                if (++spins > (1u << 22)) __trap();
            } while (c < NCTA);
            mbar_arrive(BAR(BAR_RSTOK));
        }
        return;
    }

    const int g = lane >> 2, t = lane & 3;
    uint32_t xw[9];
    {
        const uint32_t* xr = (const uint32_t*)(prm.x + warp * DM);
#pragma unroll
        for (int j = 0; j < 9; j++) xw[j] = __ldg(xr + j * 32 + lane);
    }
    const int qb = tid / 18, qq = tid - qb * 18;
    uint2 xres = make_uint2(0, 0);
    if (tid < 144) {
        xres = __ldg((const uint2*)(prm.x + qb * DM + r * 72 + qq * 4));
    }
    layernorm_row(xw);
    DBG_T(18);
    {
        uint32_t* act = (uint32_t*)(smem + SM_R2) + warp * (PITCH / 2);
#pragma unroll
        for (int j = 0; j < 9; j++) act[j * 32 + lane] = xw[j];
    }
    asm volatile("bar.sync 0, 320;" ::: "memory");
    asm volatile("barrier.cluster.arrive.relaxed.aligned;" ::: "memory");
    DBG_T(2);

    {
        const int m = warp & 3, kh = warp >> 2;
#pragma unroll
        for (int j = 0; j < 5; j++) mbar_wait(BAR(BAR_FULL + j), 0);
        DBG_T(19);
        float ca[4] = {0.f, 0.f, 0.f, 0.f}, cb[4] = {0.f, 0.f, 0.f, 0.f};
        const int lrow = (lane & 7) + ((lane >> 4) & 1) * 8;
        const int lchunk = m * 2 + ((lane >> 3) & 1);
        const uint32_t baddr = sb + SM_R2 + (lane & 7) * (PITCH * 2) + (lane >> 3) * 16;
        uint32_t bfr[9][4], afr[18][4];
#pragma unroll
        for (int s = 0; s < 9; s++) {
            const int ks = kh * 18 + 2 * s;
            ldsm_x4(bfr[s][0], bfr[s][1], bfr[s][2], bfr[s][3], baddr + ks * 32);
            const int row0 = ks * 16 + lrow, row1 = row0 + 16;
            ldsm_x4_t(afr[2 * s][0], afr[2 * s][1], afr[2 * s][2], afr[2 * s][3], sb + row0 * 128 + ((lchunk ^ (row0 & 7)) << 4));
            ldsm_x4_t(afr[2 * s + 1][0], afr[2 * s + 1][1], afr[2 * s + 1][2], afr[2 * s + 1][3], sb + row1 * 128 + ((lchunk ^ (row1 & 7)) << 4));
        }
#pragma unroll
        for (int s = 0; s < 9; s++) {
            mma16816(ca, afr[2 * s][0], afr[2 * s][1], afr[2 * s][2], afr[2 * s][3], bfr[s][0], bfr[s][1]);
            mma16816(cb, afr[2 * s + 1][0], afr[2 * s + 1][1], afr[2 * s + 1][2], afr[2 * s + 1][3], bfr[s][2], bfr[s][3]);
        }
        float* red = (float*)(smem + SM_R1);
        red[(kh * 8 + 2 * t) * 64 + m * 16 + g] = ca[0] + cb[0];
        red[(kh * 8 + 2 * t + 1) * 64 + m * 16 + g] = ca[1] + cb[1];
        red[(kh * 8 + 2 * t) * 64 + m * 16 + g + 8] = ca[2] + cb[2];
        red[(kh * 8 + 2 * t + 1) * 64 + m * 16 + g + 8] = ca[3] + cb[3];
        cons_sync();
        if (warp < 4 && lane == 0) {
#pragma unroll
            for (int j = 0; j < 5; j++) mbar_arrive(BAR(BAR_EMPTY + j));
        }
        asm volatile("barrier.cluster.wait.acquire.aligned;" ::: "memory");
        if (tid < 64) {
            const int b = tid >> 3, oct = tid & 7;
            const float* p0 = red + b * 64 + oct * 8;
            const float4 u0 = *(const float4*)p0, u1 = *(const float4*)(p0 + 4);
            const float4 v0 = *(const float4*)(p0 + 512), v1 = *(const float4*)(p0 + 516);
            const uint4 w = make_uint4(bf16_pack(u0.x + v0.x, u0.y + v0.y), bf16_pack(u0.z + v0.z, u0.w + v0.w),
                                       bf16_pack(u1.x + v1.x, u1.y + v1.y), bf16_pack(u1.z + v1.z, u1.w + v1.w));
            st_async4(mapa(sb + SM_QS + (r * 64 + oct * 8) * 2, b), w, mapa(BAR(BAR_Q), b));
        }
        mbar_wait_cl(BAR(BAR_Q));
        cons_sync();
    }
    DBG_T(3);

    float4 apart = make_float4(0.f, 0.f, 0.f, 0.f);

#pragma unroll 1
    for (int u = 0; u < 2; u++) {
        {
            uint32_t bq[16];
            {
                const int pi = (g >> 1) & 1, h = g & 1;
#pragma unroll
                for (int j = 0; j < 4; j++) {
                    uint4 v = lds128(sb + SM_QS + (u * 2 + h) * 256 + (4 * (j ^ pi) + t) * 16);
                    if (g >= 4) v = make_uint4(0, 0, 0, 0);
                    bq[4 * j] = v.x; bq[4 * j + 1] = v.y; bq[4 * j + 2] = v.z; bq[4 * j + 3] = v.w;
                }
            }
            const int pig = g & 1;
            const int first = (u ? IT_KB : IT_KA) + (warp >> 2);
            int slot = first % NS; uint32_t ph = (first / NS) & 1;
            const uint32_t rowoff = ((warp & 3) * 16 + g) * 256;
            unsigned short* sc = (unsigned short*)(smem + SM_R1);
            for (int kt = warp >> 2; kt < 32; kt += 2) {
                mbar_wait(BAR(BAR_FULL + slot), ph);
                const uint32_t base = sb + slot * SLOT + rowoff;
                uint4 X[4], Y[4];
#pragma unroll
                for (int j = 0; j < 4; j++) {
                    const uint32_t a = base + (4 * (j ^ pig) + t) * 16;
                    X[j] = lds128(a); Y[j] = lds128(a + 2048);
                }
                float ca[4] = {0.f, 0.f, 0.f, 0.f}, cb[4] = {0.f, 0.f, 0.f, 0.f};
#pragma unroll
                for (int j = 0; j < 4; j++) {
                    mma16816(ca, X[j].x, Y[j].x, X[j].y, Y[j].y, bq[4 * j], bq[4 * j + 1]);
                    mma16816(cb, X[j].z, Y[j].z, X[j].w, Y[j].w, bq[4 * j + 2], bq[4 * j + 3]);
                }
                __syncwarp();
                if (lane == 0) mbar_arrive(BAR(BAR_EMPTY + slot));
                if (t == pig) {
                    const int key = kt * 64 + (warp & 3) * 16 + g;
                    const float scale = 0.08838834764831845f;
                    sc[key] = (unsigned short)bf16_bits(bf16r(ca[0] + cb[0]) * scale);
                    sc[2048 + key] = (unsigned short)bf16_bits(bf16r(ca[1] + cb[1]) * scale);
                    sc[key + 8] = (unsigned short)bf16_bits(bf16r(ca[2] + cb[2]) * scale);
                    sc[2048 + key + 8] = (unsigned short)bf16_bits(bf16r(ca[3] + cb[3]) * scale);
                }
                slot += 2; if (slot >= NS) { slot -= NS; ph ^= 1; }
            }
        }
        cons_sync();
        if (u == 0) DBG_T(4); else DBG_T(7);

        {
            const int h = tid >> 7, idx = tid & 127;
            const uint32_t a = sb + SM_R1 + h * 4096 + idx * 32;
            const uint4 u0 = lds128(a), u1 = lds128(a + 16);
            float e[16];
            e[0] = bf_lo(u0.x); e[1] = bf_hi(u0.x); e[2] = bf_lo(u0.y); e[3] = bf_hi(u0.y);
            e[4] = bf_lo(u0.z); e[5] = bf_hi(u0.z); e[6] = bf_lo(u0.w); e[7] = bf_hi(u0.w);
            e[8] = bf_lo(u1.x); e[9] = bf_hi(u1.x); e[10] = bf_lo(u1.y); e[11] = bf_hi(u1.y);
            e[12] = bf_lo(u1.z); e[13] = bf_hi(u1.z); e[14] = bf_lo(u1.w); e[15] = bf_hi(u1.w);
            float mx = e[0];
#pragma unroll
            for (int i = 1; i < 16; i++) mx = fmaxf(mx, e[i]);
            mx = warp_max(mx);
            float* stat = (float*)(smem + SM_STAT);
            if (lane == 0) stat[warp] = mx;
            cons_sync();
            mx = fmaxf(fmaxf(stat[h * 4], stat[h * 4 + 1]), fmaxf(stat[h * 4 + 2], stat[h * 4 + 3]));
            float sum = 0.f;
#pragma unroll
            for (int i = 0; i < 16; i++) { e[i] = exp2f((e[i] - mx) * 1.4426950408889634f); sum += e[i]; }
            sum = warp_sum(sum);
            if (lane == 0) stat[8 + warp] = sum;
            cons_sync();
            sum = (stat[8 + h * 4] + stat[8 + h * 4 + 1]) + (stat[8 + h * 4 + 2] + stat[8 + h * 4 + 3]);
            const float inv = __fdiv_rn(1.0f, sum);
            uint32_t w[8];
#pragma unroll
            for (int i = 0; i < 8; i++) w[i] = bf16_pack(e[2 * i] * inv, e[2 * i + 1] * inv);
            *(uint4*)(smem + SM_R1 + h * 4096 + idx * 32) = make_uint4(w[0], w[1], w[2], w[3]);
            *(uint4*)(smem + SM_R1 + h * 4096 + idx * 32 + 16) = make_uint4(w[4], w[5], w[6], w[7]);
            cons_sync();
        }
        if (u == 0) DBG_T(5);

        {
            float acc[2][4][4];
#pragma unroll
            for (int a = 0; a < 2; a++)
#pragma unroll
                for (int b = 0; b < 4; b++)
#pragma unroll
                    for (int d = 0; d < 4; d++) acc[a][b][d] = 0.f;
            const int first = (u ? IT_VB : IT_VA) + (warp >> 2);
            const bool bvalid = (g >> 1) == t;
            const uint32_t paddr = sb + SM_R1 + (g & 1) * 4096 + ((warp & 3) * 16 + 4 * t) * 2;
            const uint32_t rowoff = ((warp & 3) * 16 + 4 * t) * 256 + (g ^ (2 * t)) * 16;
            for (int vt = warp >> 2; vt < 32; vt += 2) {
                const int item = first - (warp >> 2) + vt;
                const int slot = item_slot(item);
                const uint2 pbv = lds64(paddr + vt * 128);
                const uint32_t b0 = bvalid ? pbv.x : 0u, b1 = bvalid ? pbv.y : 0u;
                mbar_wait(BAR(BAR_FULL + slot), item_par(item));
                if (u == 1 && vt == TRIG_TILE && tid == 0) mbar_arrive(BAR(BAR_TRIG));
                const uint32_t base = sb + slot * SLOT + rowoff;
                uint4 X[2][4];
#pragma unroll
                for (int hf = 0; hf < 2; hf++)
#pragma unroll
                    for (int i = 0; i < 4; i++) X[hf][i] = lds128(base + i * 256 + hf * 128);
#pragma unroll
                for (int hf = 0; hf < 2; hf++) {
                    const uint32_t x0[4] = {X[hf][0].x, X[hf][0].y, X[hf][0].z, X[hf][0].w};
                    const uint32_t x1[4] = {X[hf][1].x, X[hf][1].y, X[hf][1].z, X[hf][1].w};
                    const uint32_t x2[4] = {X[hf][2].x, X[hf][2].y, X[hf][2].z, X[hf][2].w};
                    const uint32_t x3[4] = {X[hf][3].x, X[hf][3].y, X[hf][3].z, X[hf][3].w};
#pragma unroll
                    for (int m = 0; m < 4; m++) {
                        mma16816(acc[hf][m], __byte_perm(x0[m], x1[m], 0x5410), __byte_perm(x0[m], x1[m], 0x7632),
                                 __byte_perm(x2[m], x3[m], 0x5410), __byte_perm(x2[m], x3[m], 0x7632), b0, b1);
                    }
                }
                __syncwarp();
                if (lane == 0) mbar_arrive(BAR(BAR_EMPTY + slot));
            }
            if (u == 0) DBG_T(6); else DBG_T(8);
            if (W2_TRIG == 1 && u == 1 && tid == 0) mbar_arrive(BAR(BAR_W2GO));
            float k1[4][4];
            {
                const bool up = (t & 2) != 0;
#pragma unroll
                for (int m = 0; m < 4; m++)
#pragma unroll
                    for (int d = 0; d < 4; d++) {
                        const float keep = up ? acc[1][m][d] : acc[0][m][d];
                        const float send = up ? acc[0][m][d] : acc[1][m][d];
                        k1[m][d] = keep + __shfl_xor_sync(0xffffffffu, send, 18);
                    }
            }
            float k2[2][4];
            {
                const bool up = (t & 1) != 0;
#pragma unroll
                for (int m = 0; m < 2; m++)
#pragma unroll
                    for (int d = 0; d < 4; d++) {
                        const float keep = up ? k1[2 + m][d] : k1[m][d];
                        const float send = up ? k1[m][d] : k1[2 + m][d];
                        k2[m][d] = keep + __shfl_xor_sync(0xffffffffu, send, 9);
                    }
            }
            float* red = (float*)(smem + SM_R2);
            {
                const int d0 = ((g ^ (2 * t)) + 8 * (t >> 1)) * 8 + (t & 1) * 4;
                *(float4*)(red + warp * 256 + d0) = make_float4(k2[0][0], k2[0][2], k2[1][0], k2[1][2]);
                *(float4*)(red + warp * 256 + 128 + d0) = make_float4(k2[0][1], k2[0][3], k2[1][1], k2[1][3]);
            }
            cons_sync();
            float s = 0.f;
#pragma unroll
            for (int w = 0; w < 8; w++) s += red[w * 256 + tid];
            ((unsigned short*)(smem + SM_OL))[tid] = (unsigned short)bf16_bits(s);
            cons_sync();
            const uint4 ov = lds128(sb + SM_OL + lane * 16);
            const uint32_t obuf = sb + SM_R3 + u * (NB * OPITCH * 2);
            const uint32_t obar = BAR(u ? BAR_OB : BAR_OA);
            st_async4(mapa(obuf + r * (OPITCH * 2) + lane * 16, warp), ov, mapa(obar, warp));
            if (u == 0) {
#pragma unroll
                for (int j = 0; j < 3; j++) mbar_wait(BAR(BAR_FULL + (IT_WOA + j) % NS), ((IT_WOA + j) / NS) & 1);
            } else {
#pragma unroll
                for (int j = 0; j < 3; j++) mbar_wait(BAR(BAR_TW + j), 0);
            }
            const uint32_t wbase = u ? sb + TAIL : sb + (IT_WOA % NS) * SLOT;
            const uint32_t wstride = u ? CHUNK : SLOT;
            uint32_t af[4][3][4];
            gemv_load<4>(af, [&](int k) { return wbase + k * wstride; }, tid);
            mbar_wait_cl(obar);
            if (W2_TRIG == 2 && u == 1 && tid == 0) mbar_arrive(BAR(BAR_W2GO));
            if (u == 1) DBG_T(9);
            const float4 p = gemv_mma<4>(af, obuf, OPITCH, (float*)(smem + SM_R2), tid);
            apart.x += p.x; apart.y += p.y; apart.z += p.z; apart.w += p.w;
            if (u == 0) {
                if (warp < 4 && lane == 0) {
#pragma unroll
                    for (int j = 0; j < 3; j++) mbar_arrive(BAR(BAR_EMPTY + (IT_WOA + j) % NS));
                }
                cons_sync();
            }
        }
    }

    uint32_t hw0 = 0, hw1 = 0;
    uint32_t af[9][3][4];
    if (tid < 144) {
        mbar_wait(BAR(BAR_RSTOK), 0);
        st_pub4(&g_scr.ap[r][cl][tid * 4], make_uint4(f2pub(apart.x), f2pub(apart.y), f2pub(apart.z), f2pub(apart.w)));
        if (W2_TRIG == 3 && tid == 0) mbar_arrive(BAR(BAR_W2GO));
        if (WOFREE_EARLY && tid == 0) mbar_arrive(BAR(BAR_WOFREE));
        DBG_T(10);
    }
    if (tid < 144) {
        if (POLL_DELAY > 0) { const long long c0 = clock64(); while (clock64() - c0 < POLL_DELAY) { } }
    }
    if (tid < 144) {
        uint4 v[NCL];
        const uint32_t* ap0 = &g_scr.ap[r][0][tid * 4];
        uint32_t spins = 0;
        while (true) {
#pragma unroll
            for (int c = 0; c < NCL; c++) v[c] = ld_poll4(ap0 + c * 576);
            uint32_t bad = 0;
#pragma unroll
            for (int c = 0; c < NCL; c++)
                bad |= (uint32_t)(v[c].x == SENT) | (uint32_t)(v[c].y == SENT) | (uint32_t)(v[c].z == SENT) | (uint32_t)(v[c].w == SENT);
            if (bad == 0) break;
            if (++spins > (1u << 22)) __trap();
        }
        float s0 = 0.f, s1 = 0.f, s2 = 0.f, s3 = 0.f;
#pragma unroll
        for (int c = 0; c < NCL; c++) {
            s0 += __uint_as_float(v[c].x); s1 += __uint_as_float(v[c].y);
            s2 += __uint_as_float(v[c].z); s3 += __uint_as_float(v[c].w);
        }
        if (W2_TRIG == 4 && tid == 0) mbar_arrive(BAR(BAR_W2GO));
        if (!WOFREE_EARLY && tid == 0) mbar_arrive(BAR(BAR_WOFREE));
        DBG_T(25);
        const float h0 = bf16r(bf_lo(xres.x) + bf16r(s0)), h1 = bf16r(bf_hi(xres.x) + bf16r(s1));
        const float h2 = bf16r(bf_lo(xres.y) + bf16r(s2)), h3 = bf16r(bf_hi(xres.y) + bf16r(s3));
        hw0 = bf16_pack(h0, h1); hw1 = bf16_pack(h2, h3);
        if (qb == cl) *(float4*)(smem + SM_HS + qq * 16) = make_float4(h0, h1, h2, h3);
    }
    __syncwarp();
    if (warp < 5) send_slice(hw0, hw1, sb + SM_R1, BAR(BAR_H), r, tid);
    DBG_T(11);
#pragma unroll
    for (int j = 0; j < 6; j++) mbar_wait(BAR(BAR_TW + 3 + j), 0);
    DBG_T(27);
    gemv_load<9>(af, [&](int k) { return sb + TAIL_W1 + k * CHUNK; }, tid);
    mbar_wait_cl(BAR(BAR_H));
    DBG_T(20);
    {
        uint32_t* row = (uint32_t*)(smem + SM_R1) + warp * (PITCH / 2);
        uint32_t w[9];
#pragma unroll
        for (int j = 0; j < 9; j++) w[j] = row[j * 32 + lane];
        layernorm_row(w);
#pragma unroll
        for (int j = 0; j < 9; j++) row[j * 32 + lane] = w[j];
    }
    DBG_T(21);
    cons_sync();
    DBG_T(12);

    float4 p = gemv_mma<9>(af, sb + SM_R1, PITCH, (float*)(smem + SM_R2), tid);
    {
        float a = bf16r(p.x), b = bf16r(p.y), c = bf16r(p.z), d = bf16r(p.w);
        a = (a != a) ? a : fmaxf(a, 0.f); b = (b != b) ? b : fmaxf(b, 0.f);
        c = (c != c) ? c : fmaxf(c, 0.f); d = (d != d) ? d : fmaxf(d, 0.f);
        DBG_T(22);
        __syncwarp();
        if (warp < 5) send_slice(bf16_pack(a, b), bf16_pack(c, d), sb + SM_R3, BAR(BAR_H1), r, tid);
        DBG_T(23);
    }
#pragma unroll
    for (int j = 0; j < 6; j++) mbar_wait(BAR(BAR_TW + 9 + j), 0);
    gemv_load<9>(af, [&](int k) { return k < 4 ? sb + k * SLOT : sb + TAIL + (k - 4) * CHUNK; }, tid);
    mbar_wait_cl(BAR(BAR_H1));
    cons_sync();
    DBG_T(13);
    p = gemv_mma<9>(af, sb + SM_R3, PITCH, (float*)(smem + SM_R2), tid);
    {
        if (tid < 144) {
            st_pub4(&g_scr.fp[r][cl][tid * 4], make_uint4(f2pub(p.x), f2pub(p.y), f2pub(p.z), f2pub(p.w)));
            DBG_T(14);
            if (POLL_DELAY > 0) { const long long c0 = clock64(); while (clock64() - c0 < POLL_DELAY) { } }
            const int quad = tid >> 3, c = tid & 7;
            uint4 w;
            uint32_t spins = 0;
            while (true) {
                w = ld_poll4(&g_scr.fp[r][c][cl * 72 + quad * 4]);
                if (vec_valid(w)) break;
                if (++spins > (1u << 22)) __trap();
            }
            apart = make_float4(__uint_as_float(w.x), __uint_as_float(w.y), __uint_as_float(w.z), __uint_as_float(w.w));
        } else {
            apart = make_float4(0.f, 0.f, 0.f, 0.f);
        }
        if (warp < 5) {
            __syncwarp();
#pragma unroll
            for (int o = 1; o < 8; o <<= 1) {
                apart.x += __shfl_xor_sync(0xffffffffu, apart.x, o); apart.y += __shfl_xor_sync(0xffffffffu, apart.y, o);
                apart.z += __shfl_xor_sync(0xffffffffu, apart.z, o); apart.w += __shfl_xor_sync(0xffffffffu, apart.w, o);
            }
            if (tid < 144 && (tid & 7) == 0) {
                const int quad = tid >> 3;
                const float4 h = *(const float4*)(smem + SM_HS + quad * 16);
                uint2 o;
                o.x = bf16_pack(h.x + bf16r(apart.x), h.y + bf16r(apart.y));
                o.y = bf16_pack(h.z + bf16r(apart.z), h.w + bf16r(apart.w));
                *(uint2*)(prm.out + cl * DM + r * 72 + quad * 4) = o;
            }
            if (blockIdx.x == 0 && tid == 0) g_cnt = 0;
            DBG_T(15);
        }
    }
}

typedef CUresult (*EncodeTiledFn)(CUtensorMap*, CUtensorMapDataType, cuuint32_t, void*, const cuuint64_t*, const cuuint64_t*,
                                  const cuuint32_t*, const cuuint32_t*, CUtensorMapInterleave, CUtensorMapSwizzle,
                                  CUtensorMapL2promotion, CUtensorMapFloatOOBfill);

void make_map(EncodeTiledFn fn, CUtensorMap* m, const void* ptr, uint64_t cols, uint64_t rows, uint32_t bc, uint32_t br,
              CUtensorMapSwizzle sw) {
    cuuint64_t dims[2] = {cols, rows};
    cuuint64_t strides[1] = {cols * 2};
    cuuint32_t box[2] = {bc, br};
    cuuint32_t es[2] = {1, 1};
    fn(m, CU_TENSOR_MAP_DATA_TYPE_BFLOAT16, 2, const_cast<void*>(ptr), dims, strides, box, es, CU_TENSOR_MAP_INTERLEAVE_NONE, sw,
       CU_TENSOR_MAP_L2_PROMOTION_L2_256B, CU_TENSOR_MAP_FLOAT_OOB_FILL_NONE);
}

}

extern "C" void kernel_launch(void* const* d_in, const int* in_sizes, int n_in, void* d_out, int out_size) {
    (void)in_sizes; (void)n_in; (void)out_size;
    static EncodeTiledFn enc = nullptr;
    if (!enc) {
        void* fn = nullptr;
        cudaDriverEntryPointQueryResult qr;
        cudaGetDriverEntryPoint("cuTensorMapEncodeTiled", &fn, cudaEnableDefault, &qr);
        enc = (EncodeTiledFn)fn;
        cudaFuncSetAttribute(fused_decode_kernel, cudaFuncAttributeMaxDynamicSharedMemorySize, SM_TOTAL);
    }
    CUtensorMap mq, mo, m1, m2;
    make_map(enc, &mq, d_in[3], 4096, DM, 64, 128, CU_TENSOR_MAP_SWIZZLE_128B);
    make_map(enc, &mo, d_in[4], DM, 4096, 72, 32, CU_TENSOR_MAP_SWIZZLE_NONE);
    make_map(enc, &m1, d_in[6], DFF, DM, 72, 96, CU_TENSOR_MAP_SWIZZLE_NONE);
    make_map(enc, &m2, d_in[7], DM, DFF, 72, 96, CU_TENSOR_MAP_SWIZZLE_NONE);
    Params p;
    p.x = (const __nv_bfloat16*)d_in[0];
    p.k = (const __nv_bfloat16*)d_in[1];
    p.v = (const __nv_bfloat16*)d_in[2];
    p.out = (__nv_bfloat16*)d_out;
    fused_decode_kernel<<<NCTA, 320, SM_TOTAL, cudaStreamPerThread>>>(mq, mo, m1, m2, p);
}
```

```cpp
#include <cuda_runtime.h>
#include <cuda_bf16.h>
#include <cuda.h>
#include <stdint.h>

namespace {

constexpr int NB = 8;
constexpr int DM = 576;
constexpr int HKV = 16;
constexpr int DH = 128;
constexpr int SK = 8192;
constexpr int WIN = 2048;
constexpr int DFF = 4608;
constexpr int NCL = 8;
constexpr int CS = 8;
constexpr int NCTA = NCL * CS;

constexpr int SLOT = 16384;
constexpr int NS = 12;
constexpr int IT_KA = 5, IT_VA = 37, IT_WOA = 69, IT_KB = 72, IT_VB = 104, IT_FIFO_END = 128;
constexpr int CHUNK = 96 * 144;
constexpr int TAIL = 4 * SLOT;
constexpr int TAIL_W1 = TAIL + 256 * 144;

#define POLL_DELAY 300
#define TRIG_TILE 12
#define INFLIGHT 8

constexpr int PITCH = 584;
constexpr int OPITCH = 264;
constexpr int SM_R1 = NS * SLOT;
constexpr int SM_R2 = SM_R1 + NB * PITCH * 2;
constexpr int SM_R3 = SM_R2 + NB * PITCH * 2;
constexpr int SM_QS = SM_R3 + NB * PITCH * 2;
constexpr int SM_HS = SM_QS + 1024;
constexpr int SM_OL = SM_HS + 288;
constexpr int SM_STAT = SM_OL + 512;
constexpr int SM_BAR = SM_STAT + 64;
constexpr int BAR_FULL = 0, BAR_EMPTY = 12, BAR_TW = 24, BAR_Q = 39, BAR_OA = 40, BAR_OB = 41, BAR_H = 42, BAR_H1 = 43,
              BAR_WOFREE = 44, BAR_TRIG = 45, BAR_RSTOK = 46, NBAR = 47;
constexpr int SM_DBG = SM_BAR + NBAR * 8;
constexpr int SM_TOTAL = SM_DBG + 32 * 8;
static_assert(SM_TOTAL <= 232448, "smem");
static_assert(2 * NB * OPITCH * 2 <= NB * PITCH * 2, "o_all");

constexpr uint32_t SENT = 0xffffffffu;

struct Scratch {
    uint32_t ap[CS][NCL][576];
    uint32_t fp[CS][NCL][576];
};
__device__ __align__(128) Scratch g_scr;
__device__ uint32_t g_cnt;

#define DBG_T(i) do { } while (0)

__device__ __forceinline__ uint32_t smem_u32(const void* p) { return (uint32_t)__cvta_generic_to_shared(p); }
__device__ __forceinline__ void mbar_init(uint32_t bar, uint32_t cnt) {
    asm volatile("mbarrier.init.shared::cta.b64 [%0], %1;" ::"r"(bar), "r"(cnt) : "memory");
}
__device__ __forceinline__ void mbar_expect_tx(uint32_t bar, uint32_t bytes) {
    asm volatile("mbarrier.arrive.expect_tx.shared::cta.b64 _, [%0], %1;" ::"r"(bar), "r"(bytes) : "memory");
}
__device__ __forceinline__ void mbar_arrive(uint32_t bar) {
    asm volatile("mbarrier.arrive.shared::cta.b64 _, [%0];" ::"r"(bar) : "memory");
}
__device__ __forceinline__ bool mbar_try(uint32_t bar, uint32_t parity) {
    uint32_t ok;
    asm volatile("{\n.reg .pred p;\nmbarrier.try_wait.parity.shared::cta.b64 p, [%1], %2;\nselp.u32 %0, 1, 0, p;\n}"
                 : "=r"(ok) : "r"(bar), "r"(parity) : "memory");
    return ok != 0;
}
__device__ __forceinline__ void mbar_wait(uint32_t bar, uint32_t parity) {
    uint32_t spins = 0;
    while (!mbar_try(bar, parity)) {
        if (++spins > (1u << 22)) __trap();
    }
}
__device__ __forceinline__ bool mbar_try_cl(uint32_t bar, uint32_t parity) {
    uint32_t ok;
    asm volatile("{\n.reg .pred p;\nmbarrier.try_wait.parity.acquire.cluster.shared::cta.b64 p, [%1], %2;\nselp.u32 %0, 1, 0, p;\n}"
                 : "=r"(ok) : "r"(bar), "r"(parity) : "memory");
    return ok != 0;
}
__device__ __forceinline__ void mbar_wait_cl(uint32_t bar) {
    uint32_t spins = 0;
    while (!mbar_try_cl(bar, 0)) {
        if (++spins > (1u << 22)) __trap();
    }
}
__device__ __forceinline__ void bulk_g2s(uint32_t dst, const void* src, uint32_t bytes, uint32_t bar, uint64_t pol) {
    asm volatile("cp.async.bulk.shared::cluster.global.mbarrier::complete_tx::bytes.L2::cache_hint [%0], [%1], %2, [%3], %4;"
                 ::"r"(dst), "l"(src), "r"(bytes), "r"(bar), "l"(pol) : "memory");
}
__device__ __forceinline__ void tma_2d(uint32_t dst, const CUtensorMap* map, int x, int y, uint32_t bar, uint64_t pol) {
    asm volatile("cp.async.bulk.tensor.2d.shared::cluster.global.mbarrier::complete_tx::bytes.L2::cache_hint [%0], [%1, {%3, %4}], [%2], %5;"
                 ::"r"(dst), "l"(map), "r"(bar), "r"(x), "r"(y), "l"(pol) : "memory");
}
__device__ __forceinline__ void cons_sync() { asm volatile("bar.sync 1, 256;" ::: "memory"); }
__device__ __forceinline__ uint32_t mapa(uint32_t a, uint32_t rank) {
    uint32_t r; asm("mapa.shared::cluster.u32 %0, %1, %2;" : "=r"(r) : "r"(a), "r"(rank)); return r;
}
__device__ __forceinline__ void st_async4(uint32_t addr, uint4 v, uint32_t bar) {
    asm volatile("st.async.weak.shared::cluster.mbarrier::complete_tx::bytes.v4.b32 [%0], {%1,%2,%3,%4}, [%5];"
                 ::"r"(addr), "r"(v.x), "r"(v.y), "r"(v.z), "r"(v.w), "r"(bar) : "memory");
}
__device__ __forceinline__ uint4 lds128(uint32_t a) {
    uint4 v; asm volatile("ld.shared.v4.u32 {%0,%1,%2,%3}, [%4];" : "=r"(v.x), "=r"(v.y), "=r"(v.z), "=r"(v.w) : "r"(a)); return v;
}
__device__ __forceinline__ uint2 lds64(uint32_t a) {
    uint2 v; asm volatile("ld.shared.v2.u32 {%0,%1}, [%2];" : "=r"(v.x), "=r"(v.y) : "r"(a)); return v;
}
__device__ __forceinline__ void ldsm_x4(uint32_t& r0, uint32_t& r1, uint32_t& r2, uint32_t& r3, uint32_t a) {
    asm volatile("ldmatrix.sync.aligned.m8n8.x4.shared.b16 {%0,%1,%2,%3}, [%4];"
                 : "=r"(r0), "=r"(r1), "=r"(r2), "=r"(r3) : "r"(a));
}
__device__ __forceinline__ void ldsm_x2(uint32_t& r0, uint32_t& r1, uint32_t a) {
    asm volatile("ldmatrix.sync.aligned.m8n8.x2.shared.b16 {%0,%1}, [%2];" : "=r"(r0), "=r"(r1) : "r"(a));
}
__device__ __forceinline__ void ldsm_x4_t(uint32_t& r0, uint32_t& r1, uint32_t& r2, uint32_t& r3, uint32_t a) {
    asm volatile("ldmatrix.sync.aligned.m8n8.x4.trans.shared.b16 {%0,%1,%2,%3}, [%4];"
                 : "=r"(r0), "=r"(r1), "=r"(r2), "=r"(r3) : "r"(a));
}
__device__ __forceinline__ void mma16816(float (&c)[4], uint32_t a0, uint32_t a1, uint32_t a2, uint32_t a3, uint32_t b0, uint32_t b1) {
    asm volatile("mma.sync.aligned.m16n8k16.row.col.f32.bf16.bf16.f32 {%0,%1,%2,%3}, {%4,%5,%6,%7}, {%8,%9}, {%0,%1,%2,%3};"
                 : "+f"(c[0]), "+f"(c[1]), "+f"(c[2]), "+f"(c[3])
                 : "r"(a0), "r"(a1), "r"(a2), "r"(a3), "r"(b0), "r"(b1));
}
__device__ __forceinline__ uint4 ld_poll4(const uint32_t* p) {
    uint4 v;
    asm volatile("ld.relaxed.gpu.global.v4.u32 {%0,%1,%2,%3}, [%4];" : "=r"(v.x), "=r"(v.y), "=r"(v.z), "=r"(v.w) : "l"(p) : "memory");
    return v;
}
__device__ __forceinline__ void st_pub4(uint32_t* p, uint4 v) {
    asm volatile("st.relaxed.gpu.global.v4.u32 [%0], {%1,%2,%3,%4};" ::"l"(p), "r"(v.x), "r"(v.y), "r"(v.z), "r"(v.w) : "memory");
}
__device__ __forceinline__ bool vec_valid(const uint4& v) { return v.x != SENT && v.y != SENT && v.z != SENT && v.w != SENT; }
__device__ __forceinline__ uint32_t f2pub(float f) { uint32_t u = __float_as_uint(f); return u == SENT ? 0x7fffffffu : u; }

__device__ __forceinline__ uint32_t bf16_pack(float lo, float hi) {
    uint32_t r; asm("cvt.rn.bf16x2.f32 %0, %1, %2;" : "=r"(r) : "f"(hi), "f"(lo)); return r;
}
__device__ __forceinline__ uint32_t bf16_bits(float f) { return bf16_pack(f, 0.f); }
__device__ __forceinline__ float bf16r(float f) { return __uint_as_float(bf16_pack(0.f, f)); }
__device__ __forceinline__ float bf_lo(uint32_t w) { return __uint_as_float(w << 16); }
__device__ __forceinline__ float bf_hi(uint32_t w) { return __uint_as_float(w & 0xffff0000u); }
__device__ __forceinline__ float warp_sum(float v) {
#pragma unroll
    for (int o = 16; o > 0; o >>= 1) v += __shfl_xor_sync(0xffffffffu, v, o);
    return v;
}
__device__ __forceinline__ float warp_max(float v) {
#pragma unroll
    for (int o = 16; o > 0; o >>= 1) v = fmaxf(v, __shfl_xor_sync(0xffffffffu, v, o));
    return v;
}

template <bool FAST>
__device__ __forceinline__ void layernorm_row(uint32_t (&w)[9]) {
    const float x0 = __shfl_sync(0xffffffffu, bf_lo(w[0]), 0);
    float s0 = 0.f, s1 = 0.f, s2 = 0.f, q0 = 0.f, q1 = 0.f, q2 = 0.f;
#pragma unroll
    for (int j = 0; j < 3; j++) {
        const float a0 = bf_lo(w[j]) - x0, a1 = bf_hi(w[j]) - x0;
        const float b0 = bf_lo(w[3 + j]) - x0, b1 = bf_hi(w[3 + j]) - x0;
        const float c0 = bf_lo(w[6 + j]) - x0, c1 = bf_hi(w[6 + j]) - x0;
        s0 += a0 + a1; s1 += b0 + b1; s2 += c0 + c1;
        q0 = fmaf(a0, a0, fmaf(a1, a1, q0)); q1 = fmaf(b0, b0, fmaf(b1, b1, q1)); q2 = fmaf(c0, c0, fmaf(c1, c1, q2));
    }
    float s = (s0 + s1) + s2, q = (q0 + q1) + q2;
#pragma unroll
    for (int o = 16; o > 0; o >>= 1) { s += __shfl_xor_sync(0xffffffffu, s, o); q += __shfl_xor_sync(0xffffffffu, q, o); }
    const float md = s * (1.0f / 576.0f);
    const float m_b = bf16r(x0 + md);
    const float var_b = bf16r(fmaxf(q * (1.0f / 576.0f) - md * md, 0.f));
    float sq, inv;
    if (FAST) asm("sqrt.approx.f32 %0, %1;" : "=f"(sq) : "f"(bf16r(var_b + 1e-5f)));
    else sq = __fsqrt_rn(bf16r(var_b + 1e-5f));
    const float sd = bf16r(sq);
    if (FAST) asm("rcp.approx.f32 %0, %1;" : "=f"(inv) : "f"(sd));
    else inv = __frcp_rn(sd);
#pragma unroll
    for (int j = 0; j < 9; j++) {
        const uint32_t c = bf16_pack(bf_lo(w[j]) - m_b, bf_hi(w[j]) - m_b);
        w[j] = bf16_pack(bf_lo(c) * inv, bf_hi(c) * inv);
    }
}

__device__ __forceinline__ int item_slot(int i) { return i < IT_FIFO_END ? i % NS : (i - IT_FIFO_END) & 3; }
__device__ __forceinline__ uint32_t item_par(int i) { return i < IT_FIFO_END ? (i / NS) & 1 : (i < IT_FIFO_END + 4 ? 1u : 0u); }

template <int KQ, int NT, typename ChunkAddr>
__device__ __forceinline__ void gemv_load_t(uint32_t (&af)[KQ][3][4], ChunkAddr chunk_addr, int tid) {
    const int warp = tid >> 5, lane = tid & 31;
    const int kq = warp & 3, mg = warp >> 2;
    const int lrow = (lane & 7) + ((lane >> 4) & 1) * 8;
    const int lcol = ((lane >> 3) & 1) * 16;
#pragma unroll
    for (int s = 0; s < KQ; s++) {
        const int ks = kq * KQ + s;
        const uint32_t a = chunk_addr(ks / 6) + ((ks % 6) * 16 + lrow) * 144 + lcol + mg * 96;
#pragma unroll
        for (int m = 0; m < NT; m++) ldsm_x4_t(af[s][m][0], af[s][m][1], af[s][m][2], af[s][m][3], a + m * 32);
    }
}
template <int KQ, typename ChunkAddr>
__device__ __forceinline__ void gemv_load(uint32_t (&af)[KQ][3][4], ChunkAddr chunk_addr, int tid) {
    if (tid < 128) gemv_load_t<KQ, 3>(af, chunk_addr, tid);
    else gemv_load_t<KQ, 2>(af, chunk_addr, tid);
}
template <int KQ, int NT>
__device__ __forceinline__ void gemv_mma_t(const uint32_t (&af)[KQ][3][4], uint32_t act, int apitch, float* red, int tid) {
    const int warp = tid >> 5, lane = tid & 31, g = lane >> 2, t = lane & 3;
    const int kq = warp & 3, mg = warp >> 2;
    float acc[NT][4], acd[NT][4];
#pragma unroll
    for (int m = 0; m < NT; m++) {
        acc[m][0] = acc[m][1] = acc[m][2] = acc[m][3] = 0.f;
        acd[m][0] = acd[m][1] = acd[m][2] = acd[m][3] = 0.f;
    }
    const uint32_t baddr = act + (lane & 7) * (apitch * 2) + (lane >> 3) * 16 + kq * KQ * 32;
    uint32_t bf[KQ + 1][2];
#pragma unroll
    for (int s = 0; s + 1 < KQ; s += 2) ldsm_x4(bf[s][0], bf[s][1], bf[s + 1][0], bf[s + 1][1], baddr + s * 32);
    if (KQ & 1) ldsm_x2(bf[KQ - 1][0], bf[KQ - 1][1], act + (lane & 7) * (apitch * 2) + ((lane >> 3) & 1) * 16 + (kq * KQ + KQ - 1) * 32);
#pragma unroll
    for (int s = 0; s < KQ; s++) {
#pragma unroll
        for (int m = 0; m < NT; m++) {
            if (s & 1) mma16816(acd[m], af[s][m][0], af[s][m][1], af[s][m][2], af[s][m][3], bf[s][0], bf[s][1]);
            else mma16816(acc[m], af[s][m][0], af[s][m][1], af[s][m][2], af[s][m][3], bf[s][0], bf[s][1]);
        }
    }
    float* rp = red + kq * 576;
#pragma unroll
    for (int m = 0; m < NT; m++) {
        const int col = mg * 48 + m * 16 + g;
        rp[(2 * t) * 72 + col] = acc[m][0] + acd[m][0];
        rp[(2 * t + 1) * 72 + col] = acc[m][1] + acd[m][1];
        if (NT == 3 || m == 0) {
            rp[(2 * t) * 72 + col + 8] = acc[m][2] + acd[m][2];
            rp[(2 * t + 1) * 72 + col + 8] = acc[m][3] + acd[m][3];
        }
    }
}
template <int KQ>
__device__ __forceinline__ float4 gemv_mma(const uint32_t (&af)[KQ][3][4], uint32_t act, int apitch, float* red, int tid) {
    if (tid < 128) gemv_mma_t<KQ, 3>(af, act, apitch, red, tid);
    else gemv_mma_t<KQ, 2>(af, act, apitch, red, tid);
    cons_sync();
    float4 o = make_float4(0.f, 0.f, 0.f, 0.f);
    if (tid < 144) {
        const float4 p0 = *(const float4*)(red + tid * 4), p1 = *(const float4*)(red + 576 + tid * 4);
        const float4 p2 = *(const float4*)(red + 1152 + tid * 4), p3 = *(const float4*)(red + 1728 + tid * 4);
        o.x = (p0.x + p1.x) + (p2.x + p3.x); o.y = (p0.y + p1.y) + (p2.y + p3.y);
        o.z = (p0.z + p1.z) + (p2.z + p3.z); o.w = (p0.w + p1.w) + (p2.w + p3.w);
    }
    return o;
}

__device__ __forceinline__ void send_slice(uint32_t w0, uint32_t w1, uint32_t buf, uint32_t bar, int rank, int tid) {
    const uint32_t n0 = __shfl_xor_sync(0xffffffffu, w0, 1), n1 = __shfl_xor_sync(0xffffffffu, w1, 1);
    if (tid < 144) {
        const int b = tid / 18, quad = tid - b * 18, odd = quad & 1;
        const uint4 v = odd ? make_uint4(n0, n1, w0, w1) : make_uint4(w0, w1, n0, n1);
        const uint32_t a = buf + (b * PITCH + rank * 72 + (quad & ~1) * 4) * 2;
#pragma unroll
        for (int d = 0; d < 4; d++) {
            const int dest = odd * 4 + d;
            st_async4(mapa(a, dest), v, mapa(bar, dest));
        }
    }
}

struct Params {
    const __nv_bfloat16* x;
    const __nv_bfloat16* k;
    const __nv_bfloat16* v;
    __nv_bfloat16* out;
};

__global__ void __cluster_dims__(CS, 1, 1) __launch_bounds__(320, 1)
fused_decode_kernel(const __grid_constant__ CUtensorMap map_wq, const __grid_constant__ CUtensorMap map_wo,
                    const __grid_constant__ CUtensorMap map_w1, const __grid_constant__ CUtensorMap map_w2,
                    const Params prm)
{
    extern __shared__ __align__(1024) unsigned char smem[];
    const uint32_t sb = smem_u32(smem);
    const int tid = threadIdx.x, warp = tid >> 5, lane = tid & 31;
    const int cl = blockIdx.x >> 3;
    const int r = blockIdx.x & 7;
    const uint32_t bars = sb + SM_BAR;
    auto BAR = [&](int i) -> uint32_t { return bars + i * 8; };

    constexpr uint64_t pol = 0x12F0000000000000ull;
    int tid_op;
    asm volatile("mov.u32 %0, %1;" : "=r"(tid_op) : "r"(tid));
    if (tid_op == 256) {
        DBG_T(0);
#pragma unroll
        for (int k = 0; k < INFLIGHT; k++) mbar_init(BAR(BAR_FULL + k), 1);
        asm volatile("fence.mbarrier_init.release.cluster;" ::: "memory");
        const char* k0 = (const char*)prm.k + ((size_t)(r * HKV + 2 * cl) * SK + (SK - WIN)) * (DH * 2);
#pragma unroll
        for (int k = IT_KA; k < INFLIGHT; k++) {
            mbar_expect_tx(BAR(BAR_FULL + k), SLOT);
            bulk_g2s(sb + k * SLOT, k0 + (size_t)(k - IT_KA) * SLOT, SLOT, BAR(BAR_FULL + k), pol);
        }
#pragma unroll
        for (int k = 0; k < IT_KA; k++) {
            mbar_expect_tx(BAR(BAR_FULL + k), SLOT);
            tma_2d(sb + k * SLOT, &map_wq, cl * 512 + r * 64, k * 128, BAR(BAR_FULL + k), pol);
        }
        DBG_T(16);
    } else if (tid_op == 288) {
#pragma unroll 1
        for (int k = BAR_FULL + INFLIGHT; k < NBAR; k++) mbar_init(BAR(k), (k >= BAR_EMPTY && k < BAR_TW) ? 4 : 1);
        mbar_expect_tx(BAR(BAR_Q), CS * 128);
        mbar_expect_tx(BAR(BAR_OA), CS * 512);
        mbar_expect_tx(BAR(BAR_OB), CS * 512);
        mbar_expect_tx(BAR(BAR_H), CS * 1152);
        mbar_expect_tx(BAR(BAR_H1), CS * 1152);
        asm volatile("fence.mbarrier_init.release.cluster;" ::: "memory");
    }
    __syncwarp();
    if (warp == 8) {
        const char* kv[2][2];
#pragma unroll
        for (int u = 0; u < 2; u++) {
            const size_t off = ((size_t)(r * HKV + 2 * cl + u) * SK + (SK - WIN)) * (DH * 2);
            kv[u][0] = (const char*)prm.k + off;
            kv[u][1] = (const char*)prm.v + off;
        }
        auto issue_fifo = [&](int i) {
            const int slot = item_slot(i);
            const uint32_t dst = sb + slot * SLOT, fb = BAR(BAR_FULL + slot);
            if (i < IT_KA) {
                mbar_expect_tx(fb, SLOT);
                tma_2d(dst, &map_wq, cl * 512 + r * 64, i * 128, fb, pol);
            } else if (i >= IT_WOA && i < IT_KB) {
                const int j = i - IT_WOA, nb = j < 2 ? 3 : 2;
                mbar_expect_tx(fb, nb * 32 * 144);
                for (int u = 0; u < nb; u++) tma_2d(dst + u * 32 * 144, &map_wo, r * 72, cl * 512 + j * 96 + u * 32, fb, pol);
            } else {
                const char* src = i < IT_VA ? kv[0][0] + (size_t)(i - IT_KA) * SLOT
                                : i < IT_WOA ? kv[0][1] + (size_t)(i - IT_VA) * SLOT
                                : i < IT_VB ? kv[1][0] + (size_t)(i - IT_KB) * SLOT
                                            : kv[1][1] + (size_t)(i - IT_VB) * SLOT;
                mbar_expect_tx(fb, SLOT);
                bulk_g2s(dst, src, SLOT, fb, pol);
            }
        };
        int i = INFLIGHT;
        asm volatile("bar.sync 0, 320;" ::: "memory");
        asm volatile("barrier.cluster.arrive.relaxed.aligned;" ::: "memory");
        if (lane == 0) {
            for (; i < IT_FIFO_END; i++) {
                if (i >= NS) mbar_wait(BAR(BAR_EMPTY + i % NS), ((i / NS) - 1) & 1);
                mbar_wait(BAR(BAR_FULL + (i - INFLIGHT) % NS), ((i - INFLIGHT) / NS) & 1);
                issue_fifo(i);
            }
            auto issue_w1 = [&](int k) {
                mbar_expect_tx(BAR(BAR_TW + 3 + k), CHUNK);
                tma_2d(sb + TAIL_W1 + k * CHUNK, &map_w1, cl * 576 + r * 72, k * 96, BAR(BAR_TW + 3 + k), pol);
            };
            auto issue_wob = [&](int j) {
                const int nb = j < 2 ? 3 : 2;
                mbar_expect_tx(BAR(BAR_TW + j), nb * 32 * 144);
                for (int u = 0; u < nb; u++)
                    tma_2d(sb + TAIL + j * CHUNK + u * 32 * 144, &map_wo, r * 72, cl * 512 + 256 + j * 96 + u * 32, BAR(BAR_TW + j), pol);
            };
            auto issue_w2 = [&](int k, uint32_t dst) {
                mbar_expect_tx(BAR(BAR_TW + 9 + k), CHUNK);
                tma_2d(dst, &map_w2, r * 72, cl * 576 + k * 96, BAR(BAR_TW + 9 + k), pol);
            };
            mbar_wait(BAR(BAR_EMPTY + 8), 1); mbar_wait(BAR(BAR_EMPTY + 9), 1);
            mbar_wait(BAR(BAR_EMPTY + 10), 1); mbar_wait(BAR(BAR_EMPTY + 11), 1);
            for (int k = 0; k < 4; k++) { mbar_wait(BAR(BAR_EMPTY + k), 0); issue_fifo(IT_FIFO_END + k); }
            mbar_wait(BAR(BAR_EMPTY + 4), 0); issue_wob(0);
            mbar_wait(BAR(BAR_EMPTY + 5), 0); issue_wob(1);
            mbar_wait(BAR(BAR_EMPTY + 6), 0); issue_wob(2);
            mbar_wait(BAR(BAR_EMPTY + 7), 0);
            for (int k = 0; k < 4; k++) { mbar_wait(BAR(BAR_EMPTY + k), 1); issue_fifo(IT_FIFO_END + 4 + k); }
            mbar_wait(BAR(BAR_FULL + 3), 0);
            for (int k = 0; k < 6; k++) issue_w1(k);
            mbar_wait(BAR(BAR_TW + 3 + 5), 0);
            for (int k = 0; k < 4; k++) { mbar_wait(BAR(BAR_EMPTY + k), 0); issue_w2(k, sb + k * SLOT); }
            mbar_wait(BAR(BAR_WOFREE), 0);
            issue_w2(4, sb + TAIL); issue_w2(5, sb + TAIL + CHUNK);
            DBG_T(1);
        }
        return;
    }

    if (warp == 9) {
        asm volatile("bar.arrive 0, 320;" ::: "memory");
        asm volatile("barrier.cluster.arrive.relaxed.aligned;" ::: "memory");
        if (lane >= 1 && lane < 4) {
            const CUtensorMap* mp = lane == 1 ? &map_wo : lane == 2 ? &map_w1 : &map_w2;
            asm volatile("prefetch.tensormap [%0];" ::"l"(mp) : "memory");
        }
        mbar_wait(BAR(BAR_TRIG), 0);
        for (int i = lane; i < 144; i += 32) {
            st_pub4(&g_scr.ap[r][cl][i * 4], make_uint4(SENT, SENT, SENT, SENT));
            st_pub4(&g_scr.fp[r][cl][i * 4], make_uint4(SENT, SENT, SENT, SENT));
        }
        __threadfence();
        __syncwarp();
        if (lane == 0) {
            __threadfence();
            asm volatile("red.relaxed.gpu.global.add.u32 [%0], 1;" ::"l"(&g_cnt) : "memory");
            uint32_t c, spins = 0;
            do {
                asm volatile("ld.acquire.gpu.global.u32 %0, [%1];" : "=r"(c) : "l"(&g_cnt) : "memory");
                if (++spins > (1u << 22)) __trap();
            } while (c < NCTA);
            mbar_arrive(BAR(BAR_RSTOK));
        }
        return;
    }

    const int g = lane >> 2, t = lane & 3;
    uint32_t xw[9];
    {
        const uint32_t* xr = (const uint32_t*)(prm.x + warp * DM);
#pragma unroll
        for (int j = 0; j < 9; j++) xw[j] = __ldg(xr + j * 32 + lane);
    }
    const int qb = tid / 18, qq = tid - qb * 18;
    uint2 xres = make_uint2(0, 0);
    if (tid < 144) {
        xres = __ldg((const uint2*)(prm.x + qb * DM + r * 72 + qq * 4));
    }
    layernorm_row<false>(xw);
    DBG_T(18);
    {
        uint32_t* act = (uint32_t*)(smem + SM_R2) + warp * (PITCH / 2);
#pragma unroll
        for (int j = 0; j < 9; j++) act[j * 32 + lane] = xw[j];
    }
    asm volatile("bar.sync 0, 320;" ::: "memory");
    asm volatile("barrier.cluster.arrive.relaxed.aligned;" ::: "memory");
    DBG_T(2);

    {
        const int m = warp & 3, kh = warp >> 2;
#pragma unroll
        for (int j = 0; j < 5; j++) mbar_wait(BAR(BAR_FULL + j), 0);
        DBG_T(19);
        float ca[4] = {0.f, 0.f, 0.f, 0.f}, cb[4] = {0.f, 0.f, 0.f, 0.f};
        const int lrow = (lane & 7) + ((lane >> 4) & 1) * 8;
        const int lchunk = m * 2 + ((lane >> 3) & 1);
        const uint32_t baddr = sb + SM_R2 + (lane & 7) * (PITCH * 2) + (lane >> 3) * 16;
        uint32_t bfr[9][4], afr[18][4];
#pragma unroll
        for (int s = 0; s < 9; s++) {
            const int ks = kh * 18 + 2 * s;
            ldsm_x4(bfr[s][0], bfr[s][1], bfr[s][2], bfr[s][3], baddr + ks * 32);
            const int row0 = ks * 16 + lrow, row1 = row0 + 16;
            ldsm_x4_t(afr[2 * s][0], afr[2 * s][1], afr[2 * s][2], afr[2 * s][3], sb + row0 * 128 + ((lchunk ^ (row0 & 7)) << 4));
            ldsm_x4_t(afr[2 * s + 1][0], afr[2 * s + 1][1], afr[2 * s + 1][2], afr[2 * s + 1][3], sb + row1 * 128 + ((lchunk ^ (row1 & 7)) << 4));
        }
#pragma unroll
        for (int s = 0; s < 9; s++) {
            mma16816(ca, afr[2 * s][0], afr[2 * s][1], afr[2 * s][2], afr[2 * s][3], bfr[s][0], bfr[s][1]);
            mma16816(cb, afr[2 * s + 1][0], afr[2 * s + 1][1], afr[2 * s + 1][2], afr[2 * s + 1][3], bfr[s][2], bfr[s][3]);
        }
        float* red = (float*)(smem + SM_R1);
        red[(kh * 8 + 2 * t) * 64 + m * 16 + g] = ca[0] + cb[0];
        red[(kh * 8 + 2 * t + 1) * 64 + m * 16 + g] = ca[1] + cb[1];
        red[(kh * 8 + 2 * t) * 64 + m * 16 + g + 8] = ca[2] + cb[2];
        red[(kh * 8 + 2 * t + 1) * 64 + m * 16 + g + 8] = ca[3] + cb[3];
        cons_sync();
        if (warp < 4 && lane == 0) {
#pragma unroll
            for (int j = 0; j < 5; j++) mbar_arrive(BAR(BAR_EMPTY + j));
        }
        asm volatile("barrier.cluster.wait.acquire.aligned;" ::: "memory");
        if (tid < 64) {
            const int b = tid >> 3, oct = tid & 7;
            const float* p0 = red + b * 64 + oct * 8;
            const float4 u0 = *(const float4*)p0, u1 = *(const float4*)(p0 + 4);
            const float4 v0 = *(const float4*)(p0 + 512), v1 = *(const float4*)(p0 + 516);
            const uint4 w = make_uint4(bf16_pack(u0.x + v0.x, u0.y + v0.y), bf16_pack(u0.z + v0.z, u0.w + v0.w),
                                       bf16_pack(u1.x + v1.x, u1.y + v1.y), bf16_pack(u1.z + v1.z, u1.w + v1.w));
            st_async4(mapa(sb + SM_QS + (r * 64 + oct * 8) * 2, b), w, mapa(BAR(BAR_Q), b));
        }
        mbar_wait_cl(BAR(BAR_Q));
        cons_sync();
    }
    DBG_T(3);

    float4 apart = make_float4(0.f, 0.f, 0.f, 0.f);

#pragma unroll 1
    for (int u = 0; u < 2; u++) {
        {
            uint32_t bq[16];
            {
                const int pi = (g >> 1) & 1, h = g & 1;
#pragma unroll
                for (int j = 0; j < 4; j++) {
                    uint4 v = lds128(sb + SM_QS + (u * 2 + h) * 256 + (4 * (j ^ pi) + t) * 16);
                    if (g >= 4) v = make_uint4(0, 0, 0, 0);
                    bq[4 * j] = v.x; bq[4 * j + 1] = v.y; bq[4 * j + 2] = v.z; bq[4 * j + 3] = v.w;
                }
            }
            const int pig = g & 1;
            const int first = (u ? IT_KB : IT_KA) + (warp >> 2);
            int slot = first % NS; uint32_t ph = (first / NS) & 1;
            const uint32_t rowoff = ((warp & 3) * 16 + g) * 256;
            unsigned short* sc = (unsigned short*)(smem + SM_R1);
            for (int kt = warp >> 2; kt < 32; kt += 2) {
                mbar_wait(BAR(BAR_FULL + slot), ph);
                const uint32_t base = sb + slot * SLOT + rowoff;
                uint4 X[4], Y[4];
#pragma unroll
                for (int j = 0; j < 4; j++) {
                    const uint32_t a = base + (4 * (j ^ pig) + t) * 16;
                    X[j] = lds128(a); Y[j] = lds128(a + 2048);
                }
                float ca[4] = {0.f, 0.f, 0.f, 0.f}, cb[4] = {0.f, 0.f, 0.f, 0.f};
#pragma unroll
                for (int j = 0; j < 4; j++) {
                    mma16816(ca, X[j].x, Y[j].x, X[j].y, Y[j].y, bq[4 * j], bq[4 * j + 1]);
                    mma16816(cb, X[j].z, Y[j].z, X[j].w, Y[j].w, bq[4 * j + 2], bq[4 * j + 3]);
                }
                __syncwarp();
                if (lane == 0) mbar_arrive(BAR(BAR_EMPTY + slot));
                if (t == pig) {
                    const int key = kt * 64 + (warp & 3) * 16 + g;
                    const float scale = 0.08838834764831845f;
                    sc[key] = (unsigned short)bf16_bits(bf16r(ca[0] + cb[0]) * scale);
                    sc[2048 + key] = (unsigned short)bf16_bits(bf16r(ca[1] + cb[1]) * scale);
                    sc[key + 8] = (unsigned short)bf16_bits(bf16r(ca[2] + cb[2]) * scale);
                    sc[2048 + key + 8] = (unsigned short)bf16_bits(bf16r(ca[3] + cb[3]) * scale);
                }
                slot += 2; if (slot >= NS) { slot -= NS; ph ^= 1; }
            }
        }
        cons_sync();
        if (u == 0) DBG_T(4); else DBG_T(7);

        {
            const int h = tid >> 7, idx = tid & 127;
            const uint32_t a = sb + SM_R1 + h * 4096 + idx * 32;
            const uint4 u0 = lds128(a), u1 = lds128(a + 16);
            float e[16];
            e[0] = bf_lo(u0.x); e[1] = bf_hi(u0.x); e[2] = bf_lo(u0.y); e[3] = bf_hi(u0.y);
            e[4] = bf_lo(u0.z); e[5] = bf_hi(u0.z); e[6] = bf_lo(u0.w); e[7] = bf_hi(u0.w);
            e[8] = bf_lo(u1.x); e[9] = bf_hi(u1.x); e[10] = bf_lo(u1.y); e[11] = bf_hi(u1.y);
            e[12] = bf_lo(u1.z); e[13] = bf_hi(u1.z); e[14] = bf_lo(u1.w); e[15] = bf_hi(u1.w);
            float mx = e[0];
#pragma unroll
            for (int i = 1; i < 16; i++) mx = fmaxf(mx, e[i]);
            mx = warp_max(mx);
            float* stat = (float*)(smem + SM_STAT);
            if (lane == 0) stat[warp] = mx;
            cons_sync();
            mx = fmaxf(fmaxf(stat[h * 4], stat[h * 4 + 1]), fmaxf(stat[h * 4 + 2], stat[h * 4 + 3]));
            float sum = 0.f;
#pragma unroll
            for (int i = 0; i < 16; i++) { e[i] = exp2f((e[i] - mx) * 1.4426950408889634f); sum += e[i]; }
            sum = warp_sum(sum);
            if (lane == 0) stat[8 + warp] = sum;
            cons_sync();
            sum = (stat[8 + h * 4] + stat[8 + h * 4 + 1]) + (stat[8 + h * 4 + 2] + stat[8 + h * 4 + 3]);
            const float inv = __fdiv_rn(1.0f, sum);
            uint32_t w[8];
#pragma unroll
            for (int i = 0; i < 8; i++) w[i] = bf16_pack(e[2 * i] * inv, e[2 * i + 1] * inv);
            *(uint4*)(smem + SM_R1 + h * 4096 + idx * 32) = make_uint4(w[0], w[1], w[2], w[3]);
            *(uint4*)(smem + SM_R1 + h * 4096 + idx * 32 + 16) = make_uint4(w[4], w[5], w[6], w[7]);
            cons_sync();
        }
        if (u == 0) DBG_T(5);

        {
            float acc[2][4][4];
#pragma unroll
            for (int a = 0; a < 2; a++)
#pragma unroll
                for (int b = 0; b < 4; b++)
#pragma unroll
                    for (int d = 0; d < 4; d++) acc[a][b][d] = 0.f;
            const int first = (u ? IT_VB : IT_VA) + (warp >> 2);
            const bool bvalid = (g >> 1) == t;
            const uint32_t paddr = sb + SM_R1 + (g & 1) * 4096 + ((warp & 3) * 16 + 4 * t) * 2;
            const uint32_t rowoff = ((warp & 3) * 16 + 4 * t) * 256 + (g ^ (2 * t)) * 16;
            for (int vt = warp >> 2; vt < 32; vt += 2) {
                const int item = first - (warp >> 2) + vt;
                const int slot = item_slot(item);
                const uint2 pbv = lds64(paddr + vt * 128);
                const uint32_t b0 = bvalid ? pbv.x : 0u, b1 = bvalid ? pbv.y : 0u;
                mbar_wait(BAR(BAR_FULL + slot), item_par(item));
                if (u == 1 && vt == TRIG_TILE && tid == 0) mbar_arrive(BAR(BAR_TRIG));
                const uint32_t base = sb + slot * SLOT + rowoff;
                uint4 X[2][4];
#pragma unroll
                for (int hf = 0; hf < 2; hf++)
#pragma unroll
                    for (int i = 0; i < 4; i++) X[hf][i] = lds128(base + i * 256 + hf * 128);
#pragma unroll
                for (int hf = 0; hf < 2; hf++) {
                    const uint32_t x0[4] = {X[hf][0].x, X[hf][0].y, X[hf][0].z, X[hf][0].w};
                    const uint32_t x1[4] = {X[hf][1].x, X[hf][1].y, X[hf][1].z, X[hf][1].w};
                    const uint32_t x2[4] = {X[hf][2].x, X[hf][2].y, X[hf][2].z, X[hf][2].w};
                    const uint32_t x3[4] = {X[hf][3].x, X[hf][3].y, X[hf][3].z, X[hf][3].w};
#pragma unroll
                    for (int m = 0; m < 4; m++) {
                        mma16816(acc[hf][m], __byte_perm(x0[m], x1[m], 0x5410), __byte_perm(x0[m], x1[m], 0x7632),
                                 __byte_perm(x2[m], x3[m], 0x5410), __byte_perm(x2[m], x3[m], 0x7632), b0, b1);
                    }
                }
                __syncwarp();
                if (lane == 0) mbar_arrive(BAR(BAR_EMPTY + slot));
            }
            if (u == 0) DBG_T(6); else DBG_T(8);
            float k1[4][4];
            {
                const bool up = (t & 2) != 0;
#pragma unroll
                for (int m = 0; m < 4; m++)
#pragma unroll
                    for (int d = 0; d < 4; d++) {
                        const float keep = up ? acc[1][m][d] : acc[0][m][d];
                        const float send = up ? acc[0][m][d] : acc[1][m][d];
                        k1[m][d] = keep + __shfl_xor_sync(0xffffffffu, send, 18);
                    }
            }
            float k2[2][4];
            {
                const bool up = (t & 1) != 0;
#pragma unroll
                for (int m = 0; m < 2; m++)
#pragma unroll
                    for (int d = 0; d < 4; d++) {
                        const float keep = up ? k1[2 + m][d] : k1[m][d];
                        const float send = up ? k1[m][d] : k1[2 + m][d];
                        k2[m][d] = keep + __shfl_xor_sync(0xffffffffu, send, 9);
                    }
            }
            float* red = (float*)(smem + SM_R2);
            {
                const int d0 = ((g ^ (2 * t)) + 8 * (t >> 1)) * 8 + (t & 1) * 4;
                *(float4*)(red + warp * 256 + d0) = make_float4(k2[0][0], k2[0][2], k2[1][0], k2[1][2]);
                *(float4*)(red + warp * 256 + 128 + d0) = make_float4(k2[0][1], k2[0][3], k2[1][1], k2[1][3]);
            }
            cons_sync();
            float s = 0.f;
#pragma unroll
            for (int w = 0; w < 8; w++) s += red[w * 256 + tid];
            const uint32_t obuf = sb + SM_R3 + u * (NB * OPITCH * 2);
            const uint32_t obar = BAR(u ? BAR_OB : BAR_OA);
            ((unsigned short*)(smem + SM_OL))[tid] = (unsigned short)bf16_bits(s);
            cons_sync();
            const uint4 ov = lds128(sb + SM_OL + lane * 16);
            st_async4(mapa(obuf + r * (OPITCH * 2) + lane * 16, warp), ov, mapa(obar, warp));
            if (u == 0) {
#pragma unroll
                for (int j = 0; j < 3; j++) mbar_wait(BAR(BAR_FULL + (IT_WOA + j) % NS), ((IT_WOA + j) / NS) & 1);
            } else {
#pragma unroll
                for (int j = 0; j < 3; j++) mbar_wait(BAR(BAR_TW + j), 0);
            }
            const uint32_t wbase = u ? sb + TAIL : sb + (IT_WOA % NS) * SLOT;
            const uint32_t wstride = u ? CHUNK : SLOT;
            uint32_t af[4][3][4];
            gemv_load<4>(af, [&](int k) { return wbase + k * wstride; }, tid);
            mbar_wait_cl(obar);
            if (u == 1) DBG_T(9);
            const float4 p = gemv_mma<4>(af, obuf, OPITCH, (float*)(smem + SM_R2), tid);
            apart.x += p.x; apart.y += p.y; apart.z += p.z; apart.w += p.w;
            if (u == 0) {
                if (warp < 4 && lane == 0) {
#pragma unroll
                    for (int j = 0; j < 3; j++) mbar_arrive(BAR(BAR_EMPTY + (IT_WOA + j) % NS));
                }
                cons_sync();
            }
        }
    }

    uint32_t hw0 = 0, hw1 = 0;
    uint32_t af[9][3][4];
    if (tid < 144) {
        mbar_wait(BAR(BAR_RSTOK), 0);
        st_pub4(&g_scr.ap[r][cl][tid * 4], make_uint4(f2pub(apart.x), f2pub(apart.y), f2pub(apart.z), f2pub(apart.w)));
        DBG_T(10);
    }
    if (tid < 144) {
        { const long long c0 = clock64(); while (clock64() - c0 < POLL_DELAY) { } }
        uint4 v[NCL];
        const uint32_t* ap0 = &g_scr.ap[r][0][tid * 4];
        uint32_t spins = 0;
        while (true) {
#pragma unroll
            for (int c = 0; c < NCL; c++) v[c] = ld_poll4(ap0 + c * 576);
            uint32_t bad = 0;
#pragma unroll
            for (int c = 0; c < NCL; c++)
                bad |= (uint32_t)(v[c].x == SENT) | (uint32_t)(v[c].y == SENT) | (uint32_t)(v[c].z == SENT) | (uint32_t)(v[c].w == SENT);
            if (bad == 0) break;
            if (++spins > (1u << 22)) __trap();
        }
        float s0 = 0.f, s1 = 0.f, s2 = 0.f, s3 = 0.f;
#pragma unroll
        for (int c = 0; c < NCL; c++) {
            s0 += __uint_as_float(v[c].x); s1 += __uint_as_float(v[c].y);
            s2 += __uint_as_float(v[c].z); s3 += __uint_as_float(v[c].w);
        }
        if (tid == 0) mbar_arrive(BAR(BAR_WOFREE));
        DBG_T(25);
        const float h0 = bf16r(bf_lo(xres.x) + bf16r(s0)), h1 = bf16r(bf_hi(xres.x) + bf16r(s1));
        const float h2 = bf16r(bf_lo(xres.y) + bf16r(s2)), h3 = bf16r(bf_hi(xres.y) + bf16r(s3));
        hw0 = bf16_pack(h0, h1); hw1 = bf16_pack(h2, h3);
        if (qb == cl) *(float4*)(smem + SM_HS + qq * 16) = make_float4(h0, h1, h2, h3);
    }
    __syncwarp();
    if (warp < 5) send_slice(hw0, hw1, sb + SM_R1, BAR(BAR_H), r, tid);
    DBG_T(11);
    {
        const int c0 = (9 * (warp & 3)) / 6;
        mbar_wait(BAR(BAR_TW + 3 + c0), 0);
        mbar_wait(BAR(BAR_TW + 3 + c0 + 1), 0);
    }
    DBG_T(27);
    gemv_load<9>(af, [&](int k) { return sb + TAIL_W1 + k * CHUNK; }, tid);
    mbar_wait_cl(BAR(BAR_H));
    DBG_T(20);
    {
        uint32_t* row = (uint32_t*)(smem + SM_R1) + warp * (PITCH / 2);
        uint32_t w[9];
#pragma unroll
        for (int j = 0; j < 9; j++) w[j] = row[j * 32 + lane];
        layernorm_row<true>(w);
#pragma unroll
        for (int j = 0; j < 9; j++) row[j * 32 + lane] = w[j];
    }
    DBG_T(21);
    cons_sync();
    DBG_T(12);

    float4 p = gemv_mma<9>(af, sb + SM_R1, PITCH, (float*)(smem + SM_R2), tid);
    {
        float a = bf16r(p.x), b = bf16r(p.y), c = bf16r(p.z), d = bf16r(p.w);
        a = (a != a) ? a : fmaxf(a, 0.f); b = (b != b) ? b : fmaxf(b, 0.f);
        c = (c != c) ? c : fmaxf(c, 0.f); d = (d != d) ? d : fmaxf(d, 0.f);
        DBG_T(22);
        __syncwarp();
        if (warp < 5) send_slice(bf16_pack(a, b), bf16_pack(c, d), sb + SM_R3, BAR(BAR_H1), r, tid);
        DBG_T(23);
    }
    {
        const int c0 = (9 * (warp & 3)) / 6;
        mbar_wait(BAR(BAR_TW + 9 + c0), 0);
        mbar_wait(BAR(BAR_TW + 9 + c0 + 1), 0);
    }
    gemv_load<9>(af, [&](int k) { return k < 4 ? sb + k * SLOT : sb + TAIL + (k - 4) * CHUNK; }, tid);
    mbar_wait_cl(BAR(BAR_H1));
    DBG_T(13);
    p = gemv_mma<9>(af, sb + SM_R3, PITCH, (float*)(smem + SM_R2), tid);
    {
        if (tid < 144) {
            st_pub4(&g_scr.fp[r][cl][tid * 4], make_uint4(f2pub(p.x), f2pub(p.y), f2pub(p.z), f2pub(p.w)));
            DBG_T(14);
            { const long long c0 = clock64(); while (clock64() - c0 < POLL_DELAY) { } }
            const int quad = tid >> 3, c = tid & 7;
            uint4 w;
            uint32_t spins = 0;
            while (true) {
                w = ld_poll4(&g_scr.fp[r][c][cl * 72 + quad * 4]);
                if (vec_valid(w)) break;
                if (++spins > (1u << 22)) __trap();
            }
            apart = make_float4(__uint_as_float(w.x), __uint_as_float(w.y), __uint_as_float(w.z), __uint_as_float(w.w));
        } else {
            apart = make_float4(0.f, 0.f, 0.f, 0.f);
        }
        if (warp < 5) {
            __syncwarp();
#pragma unroll
            for (int o = 1; o < 8; o <<= 1) {
                apart.x += __shfl_xor_sync(0xffffffffu, apart.x, o); apart.y += __shfl_xor_sync(0xffffffffu, apart.y, o);
                apart.z += __shfl_xor_sync(0xffffffffu, apart.z, o); apart.w += __shfl_xor_sync(0xffffffffu, apart.w, o);
            }
            if (tid < 144 && (tid & 7) == 0) {
                const int quad = tid >> 3;
                const float4 h = *(const float4*)(smem + SM_HS + quad * 16);
                uint2 o;
                o.x = bf16_pack(h.x + bf16r(apart.x), h.y + bf16r(apart.y));
                o.y = bf16_pack(h.z + bf16r(apart.z), h.w + bf16r(apart.w));
                *(uint2*)(prm.out + cl * DM + r * 72 + quad * 4) = o;
            }
            if (blockIdx.x == 0 && tid == 0) g_cnt = 0;
            DBG_T(15);
        }
    }
}

typedef CUresult (*EncodeTiledFn)(CUtensorMap*, CUtensorMapDataType, cuuint32_t, void*, const cuuint64_t*, const cuuint64_t*,
                                  const cuuint32_t*, const cuuint32_t*, CUtensorMapInterleave, CUtensorMapSwizzle,
                                  CUtensorMapL2promotion, CUtensorMapFloatOOBfill);

void make_map(EncodeTiledFn fn, CUtensorMap* m, const void* ptr, uint64_t cols, uint64_t rows, uint32_t bc, uint32_t br,
              CUtensorMapSwizzle sw) {
    cuuint64_t dims[2] = {cols, rows};
    cuuint64_t strides[1] = {cols * 2};
    cuuint32_t box[2] = {bc, br};
    cuuint32_t es[2] = {1, 1};
    fn(m, CU_TENSOR_MAP_DATA_TYPE_BFLOAT16, 2, const_cast<void*>(ptr), dims, strides, box, es, CU_TENSOR_MAP_INTERLEAVE_NONE, sw,
       CU_TENSOR_MAP_L2_PROMOTION_L2_256B, CU_TENSOR_MAP_FLOAT_OOB_FILL_NONE);
}

}

extern "C" void kernel_launch(void* const* d_in, const int* in_sizes, int n_in, void* d_out, int out_size) {
    (void)in_sizes; (void)n_in; (void)out_size;
    static EncodeTiledFn enc = nullptr;
    if (!enc) {
        void* fn = nullptr;
        cudaDriverEntryPointQueryResult qr;
        cudaGetDriverEntryPoint("cuTensorMapEncodeTiled", &fn, cudaEnableDefault, &qr);
        enc = (EncodeTiledFn)fn;
        cudaFuncSetAttribute(fused_decode_kernel, cudaFuncAttributeMaxDynamicSharedMemorySize, SM_TOTAL);
    }
    CUtensorMap mq, mo, m1, m2;
    make_map(enc, &mq, d_in[3], 4096, DM, 64, 128, CU_TENSOR_MAP_SWIZZLE_128B);
    make_map(enc, &mo, d_in[4], DM, 4096, 72, 32, CU_TENSOR_MAP_SWIZZLE_NONE);
    make_map(enc, &m1, d_in[6], DFF, DM, 72, 96, CU_TENSOR_MAP_SWIZZLE_NONE);
    make_map(enc, &m2, d_in[7], DM, DFF, 72, 96, CU_TENSOR_MAP_SWIZZLE_NONE);
    Params p;
    p.x = (const __nv_bfloat16*)d_in[0];
    p.k = (const __nv_bfloat16*)d_in[1];
    p.v = (const __nv_bfloat16*)d_in[2];
    p.out = (__nv_bfloat16*)d_out;
    fused_decode_kernel<<<NCTA, 320, SM_TOTAL, cudaStreamPerThread>>>(mq, mo, m1, m2, p);
}
```

```cpp
#include <cuda_runtime.h>
#include <cuda_bf16.h>
#include <cuda.h>
#include <stdint.h>

namespace {

constexpr int NB = 8;
constexpr int DM = 576;
constexpr int HKV = 16;
constexpr int DH = 128;
constexpr int SK = 8192;
constexpr int WIN = 2048;
constexpr int DFF = 4608;
constexpr int NCL = 8;
constexpr int CS = 8;
constexpr int NCTA = NCL * CS;

constexpr int SLOT = 16384;
constexpr int NS = 12;
constexpr int IT_KA = 5, IT_VA = 37, IT_WOA = 69, IT_KB = 72, IT_VB = 104, IT_FIFO_END = 128;
constexpr int CHUNK = 96 * 144;
constexpr int TAIL = 4 * SLOT;
constexpr int TAIL_W1 = TAIL + 256 * 144;

#define POLL_DELAY 300
#define TRIG_TILE 12
#define BURST 6
#define KFIRST 0
#define INFLIGHT 10

constexpr int PITCH = 584;
constexpr int OPITCH = 264;
constexpr int SM_R1 = NS * SLOT;
constexpr int SM_R2 = SM_R1 + NB * PITCH * 2;
constexpr int SM_R3 = SM_R2 + NB * PITCH * 2;
constexpr int SM_QS = SM_R3 + NB * PITCH * 2;
constexpr int SM_HS = SM_QS + 1024;
constexpr int SM_OL = SM_HS + 288;
constexpr int SM_STAT = SM_OL + 512;
constexpr int SM_BAR = SM_STAT + 64;
constexpr int BAR_FULL = 0, BAR_EMPTY = 12, BAR_TW = 24, BAR_Q = 39, BAR_OA = 40, BAR_OB = 41, BAR_H = 42, BAR_H1 = 43,
              BAR_WOFREE = 44, BAR_TRIG = 45, BAR_RSTOK = 46, NBAR = 47;
constexpr int SM_DBG = SM_BAR + NBAR * 8;
constexpr int SM_TOTAL = SM_DBG + 32 * 8;
static_assert(SM_TOTAL <= 232448, "smem");
static_assert(2 * NB * OPITCH * 2 <= NB * PITCH * 2, "o_all");

constexpr uint32_t SENT = 0xffffffffu;

struct Scratch {
    uint32_t ap[CS][NCL][576];
    uint32_t fp[CS][NCL][576];
};
__device__ __align__(128) Scratch g_scr;
__device__ uint32_t g_cnt;

#define DBG_T(i) do { } while (0)

__device__ __forceinline__ uint32_t smem_u32(const void* p) { return (uint32_t)__cvta_generic_to_shared(p); }
__device__ __forceinline__ void mbar_init(uint32_t bar, uint32_t cnt) {
    asm volatile("mbarrier.init.shared::cta.b64 [%0], %1;" ::"r"(bar), "r"(cnt) : "memory");
}
__device__ __forceinline__ void mbar_expect_tx(uint32_t bar, uint32_t bytes) {
    asm volatile("mbarrier.arrive.expect_tx.shared::cta.b64 _, [%0], %1;" ::"r"(bar), "r"(bytes) : "memory");
}
__device__ __forceinline__ void mbar_arrive(uint32_t bar) {
    asm volatile("mbarrier.arrive.shared::cta.b64 _, [%0];" ::"r"(bar) : "memory");
}
__device__ __forceinline__ bool mbar_try(uint32_t bar, uint32_t parity) {
    uint32_t ok;
    asm volatile("{\n.reg .pred p;\nmbarrier.try_wait.parity.shared::cta.b64 p, [%1], %2;\nselp.u32 %0, 1, 0, p;\n}"
                 : "=r"(ok) : "r"(bar), "r"(parity) : "memory");
    return ok != 0;
}
__device__ __forceinline__ void mbar_wait(uint32_t bar, uint32_t parity) {
    uint32_t spins = 0;
    while (!mbar_try(bar, parity)) {
        if (++spins > (1u << 22)) __trap();
    }
}
__device__ __forceinline__ bool mbar_try_cl(uint32_t bar, uint32_t parity) {
    uint32_t ok;
    asm volatile("{\n.reg .pred p;\nmbarrier.try_wait.parity.acquire.cluster.shared::cta.b64 p, [%1], %2;\nselp.u32 %0, 1, 0, p;\n}"
                 : "=r"(ok) : "r"(bar), "r"(parity) : "memory");
    return ok != 0;
}
__device__ __forceinline__ void mbar_wait_cl(uint32_t bar) {
    uint32_t spins = 0;
    while (!mbar_try_cl(bar, 0)) {
        if (++spins > (1u << 22)) __trap();
    }
}
__device__ __forceinline__ void bulk_g2s(uint32_t dst, const void* src, uint32_t bytes, uint32_t bar, uint64_t pol) {
    asm volatile("cp.async.bulk.shared::cluster.global.mbarrier::complete_tx::bytes.L2::cache_hint [%0], [%1], %2, [%3], %4;"
                 ::"r"(dst), "l"(src), "r"(bytes), "r"(bar), "l"(pol) : "memory");
}
__device__ __forceinline__ void tma_2d(uint32_t dst, const CUtensorMap* map, int x, int y, uint32_t bar, uint64_t pol) {
    asm volatile("cp.async.bulk.tensor.2d.shared::cluster.global.mbarrier::complete_tx::bytes.L2::cache_hint [%0], [%1, {%3, %4}], [%2], %5;"
                 ::"r"(dst), "l"(map), "r"(bar), "r"(x), "r"(y), "l"(pol) : "memory");
}
__device__ __forceinline__ void cons_sync() { asm volatile("bar.sync 1, 256;" ::: "memory"); }
__device__ __forceinline__ uint32_t mapa(uint32_t a, uint32_t rank) {
    uint32_t r; asm("mapa.shared::cluster.u32 %0, %1, %2;" : "=r"(r) : "r"(a), "r"(rank)); return r;
}
__device__ __forceinline__ void st_async4(uint32_t addr, uint4 v, uint32_t bar) {
    asm volatile("st.async.weak.shared::cluster.mbarrier::complete_tx::bytes.v4.b32 [%0], {%1,%2,%3,%4}, [%5];"
                 ::"r"(addr), "r"(v.x), "r"(v.y), "r"(v.z), "r"(v.w), "r"(bar) : "memory");
}
__device__ __forceinline__ uint4 lds128(uint32_t a) {
    uint4 v; asm volatile("ld.shared.v4.u32 {%0,%1,%2,%3}, [%4];" : "=r"(v.x), "=r"(v.y), "=r"(v.z), "=r"(v.w) : "r"(a)); return v;
}
__device__ __forceinline__ uint2 lds64(uint32_t a) {
    uint2 v; asm volatile("ld.shared.v2.u32 {%0,%1}, [%2];" : "=r"(v.x), "=r"(v.y) : "r"(a)); return v;
}
__device__ __forceinline__ void ldsm_x4(uint32_t& r0, uint32_t& r1, uint32_t& r2, uint32_t& r3, uint32_t a) {
    asm volatile("ldmatrix.sync.aligned.m8n8.x4.shared.b16 {%0,%1,%2,%3}, [%4];"
                 : "=r"(r0), "=r"(r1), "=r"(r2), "=r"(r3) : "r"(a));
}
__device__ __forceinline__ void ldsm_x2(uint32_t& r0, uint32_t& r1, uint32_t a) {
    asm volatile("ldmatrix.sync.aligned.m8n8.x2.shared.b16 {%0,%1}, [%2];" : "=r"(r0), "=r"(r1) : "r"(a));
}
__device__ __forceinline__ void ldsm_x4_t(uint32_t& r0, uint32_t& r1, uint32_t& r2, uint32_t& r3, uint32_t a) {
    asm volatile("ldmatrix.sync.aligned.m8n8.x4.trans.shared.b16 {%0,%1,%2,%3}, [%4];"
                 : "=r"(r0), "=r"(r1), "=r"(r2), "=r"(r3) : "r"(a));
}
__device__ __forceinline__ void mma16816(float (&c)[4], uint32_t a0, uint32_t a1, uint32_t a2, uint32_t a3, uint32_t b0, uint32_t b1) {
    asm volatile("mma.sync.aligned.m16n8k16.row.col.f32.bf16.bf16.f32 {%0,%1,%2,%3}, {%4,%5,%6,%7}, {%8,%9}, {%0,%1,%2,%3};"
                 : "+f"(c[0]), "+f"(c[1]), "+f"(c[2]), "+f"(c[3])
                 : "r"(a0), "r"(a1), "r"(a2), "r"(a3), "r"(b0), "r"(b1));
}
__device__ __forceinline__ uint4 ld_poll4(const uint32_t* p) {
    uint4 v;
    asm volatile("ld.relaxed.gpu.global.v4.u32 {%0,%1,%2,%3}, [%4];" : "=r"(v.x), "=r"(v.y), "=r"(v.z), "=r"(v.w) : "l"(p) : "memory");
    return v;
}
__device__ __forceinline__ void st_pub4(uint32_t* p, uint4 v) {
    asm volatile("st.relaxed.gpu.global.v4.u32 [%0], {%1,%2,%3,%4};" ::"l"(p), "r"(v.x), "r"(v.y), "r"(v.z), "r"(v.w) : "memory");
}
__device__ __forceinline__ bool vec_valid(const uint4& v) { return v.x != SENT && v.y != SENT && v.z != SENT && v.w != SENT; }
__device__ __forceinline__ uint32_t f2pub(float f) { uint32_t u = __float_as_uint(f); return u == SENT ? 0x7fffffffu : u; }

__device__ __forceinline__ uint32_t bf16_pack(float lo, float hi) {
    uint32_t r; asm("cvt.rn.bf16x2.f32 %0, %1, %2;" : "=r"(r) : "f"(hi), "f"(lo)); return r;
}
__device__ __forceinline__ uint32_t bf16_bits(float f) { return bf16_pack(f, 0.f); }
__device__ __forceinline__ float bf16r(float f) { return __uint_as_float(bf16_pack(0.f, f)); }
__device__ __forceinline__ float bf_lo(uint32_t w) { return __uint_as_float(w << 16); }
__device__ __forceinline__ float bf_hi(uint32_t w) { return __uint_as_float(w & 0xffff0000u); }
__device__ __forceinline__ float warp_sum(float v) {
#pragma unroll
    for (int o = 16; o > 0; o >>= 1) v += __shfl_xor_sync(0xffffffffu, v, o);
    return v;
}
__device__ __forceinline__ float warp_max(float v) {
#pragma unroll
    for (int o = 16; o > 0; o >>= 1) v = fmaxf(v, __shfl_xor_sync(0xffffffffu, v, o));
    return v;
}

template <bool FAST>
__device__ __forceinline__ void layernorm_row(uint32_t (&w)[9]) {
    const float x0 = __shfl_sync(0xffffffffu, bf_lo(w[0]), 0);
    float s0 = 0.f, s1 = 0.f, s2 = 0.f, q0 = 0.f, q1 = 0.f, q2 = 0.f;
#pragma unroll
    for (int j = 0; j < 3; j++) {
        const float a0 = bf_lo(w[j]) - x0, a1 = bf_hi(w[j]) - x0;
        const float b0 = bf_lo(w[3 + j]) - x0, b1 = bf_hi(w[3 + j]) - x0;
        const float c0 = bf_lo(w[6 + j]) - x0, c1 = bf_hi(w[6 + j]) - x0;
        s0 += a0 + a1; s1 += b0 + b1; s2 += c0 + c1;
        q0 = fmaf(a0, a0, fmaf(a1, a1, q0)); q1 = fmaf(b0, b0, fmaf(b1, b1, q1)); q2 = fmaf(c0, c0, fmaf(c1, c1, q2));
    }
    float s = (s0 + s1) + s2, q = (q0 + q1) + q2;
#pragma unroll
    for (int o = 16; o > 0; o >>= 1) { s += __shfl_xor_sync(0xffffffffu, s, o); q += __shfl_xor_sync(0xffffffffu, q, o); }
    const float md = s * (1.0f / 576.0f);
    const float m_b = bf16r(x0 + md);
    const float var_b = bf16r(fmaxf(q * (1.0f / 576.0f) - md * md, 0.f));
    float sq, inv;
    if (FAST) asm("sqrt.approx.f32 %0, %1;" : "=f"(sq) : "f"(bf16r(var_b + 1e-5f)));
    else sq = __fsqrt_rn(bf16r(var_b + 1e-5f));
    const float sd = bf16r(sq);
    if (FAST) asm("rcp.approx.f32 %0, %1;" : "=f"(inv) : "f"(sd));
    else inv = __frcp_rn(sd);
#pragma unroll
    for (int j = 0; j < 9; j++) {
        const uint32_t c = bf16_pack(bf_lo(w[j]) - m_b, bf_hi(w[j]) - m_b);
        w[j] = bf16_pack(bf_lo(c) * inv, bf_hi(c) * inv);
    }
}

__device__ __forceinline__ int item_slot(int i) { return i < IT_FIFO_END ? i % NS : (i - IT_FIFO_END) & 3; }
__device__ __forceinline__ uint32_t item_par(int i) { return i < IT_FIFO_END ? (i / NS) & 1 : (i < IT_FIFO_END + 4 ? 1u : 0u); }

template <int KQ, int NT, typename ChunkAddr>
__device__ __forceinline__ void gemv_load_t(uint32_t (&af)[KQ][3][4], ChunkAddr chunk_addr, int tid) {
    const int warp = tid >> 5, lane = tid & 31;
    const int kq = warp & 3, mg = warp >> 2;
    const int lrow = (lane & 7) + ((lane >> 4) & 1) * 8;
    const int lcol = ((lane >> 3) & 1) * 16;
#pragma unroll
    for (int s = 0; s < KQ; s++) {
        const int ks = kq * KQ + s;
        const uint32_t a = chunk_addr(ks / 6) + ((ks % 6) * 16 + lrow) * 144 + lcol + mg * 96;
#pragma unroll
        for (int m = 0; m < NT; m++) ldsm_x4_t(af[s][m][0], af[s][m][1], af[s][m][2], af[s][m][3], a + m * 32);
    }
}
template <int KQ, typename ChunkAddr>
__device__ __forceinline__ void gemv_load(uint32_t (&af)[KQ][3][4], ChunkAddr chunk_addr, int tid) {
    if (tid < 128) gemv_load_t<KQ, 3>(af, chunk_addr, tid);
    else gemv_load_t<KQ, 2>(af, chunk_addr, tid);
}
template <int KQ, int NT>
__device__ __forceinline__ void gemv_mma_t(const uint32_t (&af)[KQ][3][4], uint32_t act, int apitch, float* red, int tid) {
    const int warp = tid >> 5, lane = tid & 31, g = lane >> 2, t = lane & 3;
    const int kq = warp & 3, mg = warp >> 2;
    float acc[NT][4], acd[NT][4];
#pragma unroll
    for (int m = 0; m < NT; m++) {
        acc[m][0] = acc[m][1] = acc[m][2] = acc[m][3] = 0.f;
        acd[m][0] = acd[m][1] = acd[m][2] = acd[m][3] = 0.f;
    }
    const uint32_t baddr = act + (lane & 7) * (apitch * 2) + (lane >> 3) * 16 + kq * KQ * 32;
    uint32_t bf[KQ + 1][2];
#pragma unroll
    for (int s = 0; s + 1 < KQ; s += 2) ldsm_x4(bf[s][0], bf[s][1], bf[s + 1][0], bf[s + 1][1], baddr + s * 32);
    if (KQ & 1) ldsm_x2(bf[KQ - 1][0], bf[KQ - 1][1], act + (lane & 7) * (apitch * 2) + ((lane >> 3) & 1) * 16 + (kq * KQ + KQ - 1) * 32);
#pragma unroll
    for (int s = 0; s < KQ; s++) {
#pragma unroll
        for (int m = 0; m < NT; m++) {
            if (s & 1) mma16816(acd[m], af[s][m][0], af[s][m][1], af[s][m][2], af[s][m][3], bf[s][0], bf[s][1]);
            else mma16816(acc[m], af[s][m][0], af[s][m][1], af[s][m][2], af[s][m][3], bf[s][0], bf[s][1]);
        }
    }
    float* rp = red + kq * 576;
#pragma unroll
    for (int m = 0; m < NT; m++) {
        const int col = mg * 48 + m * 16 + g;
        rp[(2 * t) * 72 + col] = acc[m][0] + acd[m][0];
        rp[(2 * t + 1) * 72 + col] = acc[m][1] + acd[m][1];
        if (NT == 3 || m == 0) {
            rp[(2 * t) * 72 + col + 8] = acc[m][2] + acd[m][2];
            rp[(2 * t + 1) * 72 + col + 8] = acc[m][3] + acd[m][3];
        }
    }
}
template <int KQ>
__device__ __forceinline__ float4 gemv_mma(const uint32_t (&af)[KQ][3][4], uint32_t act, int apitch, float* red, int tid) {
    if (tid < 128) gemv_mma_t<KQ, 3>(af, act, apitch, red, tid);
    else gemv_mma_t<KQ, 2>(af, act, apitch, red, tid);
    cons_sync();
    float4 o = make_float4(0.f, 0.f, 0.f, 0.f);
    if (tid < 144) {
        const float4 p0 = *(const float4*)(red + tid * 4), p1 = *(const float4*)(red + 576 + tid * 4);
        const float4 p2 = *(const float4*)(red + 1152 + tid * 4), p3 = *(const float4*)(red + 1728 + tid * 4);
        o.x = (p0.x + p1.x) + (p2.x + p3.x); o.y = (p0.y + p1.y) + (p2.y + p3.y);
        o.z = (p0.z + p1.z) + (p2.z + p3.z); o.w = (p0.w + p1.w) + (p2.w + p3.w);
    }
    return o;
}

__device__ __forceinline__ void send_slice(uint32_t w0, uint32_t w1, uint32_t buf, uint32_t bar, int rank, int tid) {
    const uint32_t n0 = __shfl_xor_sync(0xffffffffu, w0, 1), n1 = __shfl_xor_sync(0xffffffffu, w1, 1);
    if (tid < 144) {
        const int b = tid / 18, quad = tid - b * 18, odd = quad & 1;
        const uint4 v = odd ? make_uint4(n0, n1, w0, w1) : make_uint4(w0, w1, n0, n1);
        const uint32_t a = buf + (b * PITCH + rank * 72 + (quad & ~1) * 4) * 2;
#pragma unroll
        for (int d = 0; d < 4; d++) {
            const int dest = odd * 4 + d;
            st_async4(mapa(a, dest), v, mapa(bar, dest));
        }
    }
}

struct Params {
    const __nv_bfloat16* x;
    const __nv_bfloat16* k;
    const __nv_bfloat16* v;
    __nv_bfloat16* out;
};

__global__ void __cluster_dims__(CS, 1, 1) __launch_bounds__(320, 1)
fused_decode_kernel(const __grid_constant__ CUtensorMap map_wq, const __grid_constant__ CUtensorMap map_wo,
                    const __grid_constant__ CUtensorMap map_w1, const __grid_constant__ CUtensorMap map_w2,
                    const Params prm)
{
    extern __shared__ __align__(1024) unsigned char smem[];
    const uint32_t sb = smem_u32(smem);
    const int tid = threadIdx.x, warp = tid >> 5, lane = tid & 31;
    const int cl = blockIdx.x >> 3;
    const int r = blockIdx.x & 7;
    const uint32_t bars = sb + SM_BAR;
    auto BAR = [&](int i) -> uint32_t { return bars + i * 8; };

    constexpr uint64_t pol = 0x12F0000000000000ull;
    int tid_op;
    asm volatile("mov.u32 %0, %1;" : "=r"(tid_op) : "r"(tid));
    if (tid_op == 256) {
        DBG_T(0);
#pragma unroll
        for (int k = 0; k < BURST; k++) mbar_init(BAR(BAR_FULL + k), 1);
        asm volatile("fence.mbarrier_init.release.cluster;" ::: "memory");
        const char* k0 = (const char*)prm.k + ((size_t)(r * HKV + 2 * cl) * SK + (SK - WIN)) * (DH * 2);
#pragma unroll
        for (int k = IT_KA; k < IT_KA + KFIRST; k++) {
            mbar_expect_tx(BAR(BAR_FULL + k), SLOT);
            bulk_g2s(sb + k * SLOT, k0 + (size_t)(k - IT_KA) * SLOT, SLOT, BAR(BAR_FULL + k), pol);
        }
#pragma unroll
        for (int k = 0; k < IT_KA; k++) {
            mbar_expect_tx(BAR(BAR_FULL + k), SLOT);
            tma_2d(sb + k * SLOT, &map_wq, cl * 512 + r * 64, k * 128, BAR(BAR_FULL + k), pol);
        }
#pragma unroll
        for (int k = IT_KA + KFIRST; k < BURST; k++) {
            mbar_expect_tx(BAR(BAR_FULL + k), SLOT);
            bulk_g2s(sb + k * SLOT, k0 + (size_t)(k - IT_KA) * SLOT, SLOT, BAR(BAR_FULL + k), pol);
        }
        DBG_T(16);
    } else if (tid_op == 288) {
#pragma unroll 1
        for (int k = BAR_FULL + BURST; k < NBAR; k++) mbar_init(BAR(k), (k >= BAR_EMPTY && k < BAR_TW) ? 4 : 1);
        mbar_expect_tx(BAR(BAR_Q), CS * 128);
        mbar_expect_tx(BAR(BAR_OA), CS * 512);
        mbar_expect_tx(BAR(BAR_OB), CS * 512);
        mbar_expect_tx(BAR(BAR_H), CS * 1152);
        mbar_expect_tx(BAR(BAR_H1), CS * 1152);
        asm volatile("fence.mbarrier_init.release.cluster;" ::: "memory");
    }
    __syncwarp();
    if ((tid_op >> 5) == 9) asm volatile("bar.arrive 0, 320;" ::: "memory");
    if (warp == 8) {
        const char* kv[2][2];
#pragma unroll
        for (int u = 0; u < 2; u++) {
            const size_t off = ((size_t)(r * HKV + 2 * cl + u) * SK + (SK - WIN)) * (DH * 2);
            kv[u][0] = (const char*)prm.k + off;
            kv[u][1] = (const char*)prm.v + off;
        }
        auto issue_fifo = [&](int i) {
            const int slot = item_slot(i);
            const uint32_t dst = sb + slot * SLOT, fb = BAR(BAR_FULL + slot);
            if (i < IT_KA) {
                mbar_expect_tx(fb, SLOT);
                tma_2d(dst, &map_wq, cl * 512 + r * 64, i * 128, fb, pol);
            } else if (i >= IT_WOA && i < IT_KB) {
                const int j = i - IT_WOA, nb = j < 2 ? 3 : 2;
                mbar_expect_tx(fb, nb * 32 * 144);
                for (int u = 0; u < nb; u++) tma_2d(dst + u * 32 * 144, &map_wo, r * 72, cl * 512 + j * 96 + u * 32, fb, pol);
            } else {
                const char* src = i < IT_VA ? kv[0][0] + (size_t)(i - IT_KA) * SLOT
                                : i < IT_WOA ? kv[0][1] + (size_t)(i - IT_VA) * SLOT
                                : i < IT_VB ? kv[1][0] + (size_t)(i - IT_KB) * SLOT
                                            : kv[1][1] + (size_t)(i - IT_VB) * SLOT;
                mbar_expect_tx(fb, SLOT);
                bulk_g2s(dst, src, SLOT, fb, pol);
            }
        };
        int i = BURST;
        asm volatile("bar.sync 0, 320;" ::: "memory");
        asm volatile("barrier.cluster.arrive.relaxed.aligned;" ::: "memory");
        if (lane == 0) {
            for (; i < IT_FIFO_END; i++) {
                if (i >= NS) mbar_wait(BAR(BAR_EMPTY + i % NS), ((i / NS) - 1) & 1);
                if (i >= INFLIGHT) mbar_wait(BAR(BAR_FULL + (i - INFLIGHT) % NS), ((i - INFLIGHT) / NS) & 1);
                issue_fifo(i);
            }
            auto issue_w1 = [&](int k) {
                mbar_expect_tx(BAR(BAR_TW + 3 + k), CHUNK);
                tma_2d(sb + TAIL_W1 + k * CHUNK, &map_w1, cl * 576 + r * 72, k * 96, BAR(BAR_TW + 3 + k), pol);
            };
            auto issue_wob = [&](int j) {
                const int nb = j < 2 ? 3 : 2;
                mbar_expect_tx(BAR(BAR_TW + j), nb * 32 * 144);
                for (int u = 0; u < nb; u++)
                    tma_2d(sb + TAIL + j * CHUNK + u * 32 * 144, &map_wo, r * 72, cl * 512 + 256 + j * 96 + u * 32, BAR(BAR_TW + j), pol);
            };
            auto issue_w2 = [&](int k, uint32_t dst) {
                mbar_expect_tx(BAR(BAR_TW + 9 + k), CHUNK);
                tma_2d(dst, &map_w2, r * 72, cl * 576 + k * 96, BAR(BAR_TW + 9 + k), pol);
            };
            mbar_wait(BAR(BAR_EMPTY + 8), 1); mbar_wait(BAR(BAR_EMPTY + 9), 1);
            mbar_wait(BAR(BAR_EMPTY + 10), 1); mbar_wait(BAR(BAR_EMPTY + 11), 1);
            for (int k = 0; k < 4; k++) { mbar_wait(BAR(BAR_EMPTY + k), 0); issue_fifo(IT_FIFO_END + k); }
            mbar_wait(BAR(BAR_EMPTY + 4), 0); issue_wob(0);
            mbar_wait(BAR(BAR_EMPTY + 5), 0); issue_wob(1);
            mbar_wait(BAR(BAR_EMPTY + 6), 0); issue_wob(2);
            mbar_wait(BAR(BAR_EMPTY + 7), 0);
            for (int k = 0; k < 4; k++) { mbar_wait(BAR(BAR_EMPTY + k), 1); issue_fifo(IT_FIFO_END + 4 + k); }
            mbar_wait(BAR(BAR_FULL + 3), 0);
            for (int k = 0; k < 6; k++) issue_w1(k);
            mbar_wait(BAR(BAR_TW + 3 + 5), 0);
            for (int k = 0; k < 4; k++) { mbar_wait(BAR(BAR_EMPTY + k), 0); issue_w2(k, sb + k * SLOT); }
            mbar_wait(BAR(BAR_WOFREE), 0);
            issue_w2(4, sb + TAIL); issue_w2(5, sb + TAIL + CHUNK);
            DBG_T(1);
        }
        return;
    }

    if (warp == 9) {
        asm volatile("barrier.cluster.arrive.relaxed.aligned;" ::: "memory");
        if (lane >= 1 && lane < 4) {
            const CUtensorMap* mp = lane == 1 ? &map_wo : lane == 2 ? &map_w1 : &map_w2;
            asm volatile("prefetch.tensormap [%0];" ::"l"(mp) : "memory");
        }
        mbar_wait(BAR(BAR_TRIG), 0);
        for (int i = lane; i < 144; i += 32) {
            st_pub4(&g_scr.ap[r][cl][i * 4], make_uint4(SENT, SENT, SENT, SENT));
            st_pub4(&g_scr.fp[r][cl][i * 4], make_uint4(SENT, SENT, SENT, SENT));
        }
        __threadfence();
        __syncwarp();
        if (lane == 0) {
            __threadfence();
            asm volatile("red.relaxed.gpu.global.add.u32 [%0], 1;" ::"l"(&g_cnt) : "memory");
            uint32_t c, spins = 0;
            do {
                asm volatile("ld.acquire.gpu.global.u32 %0, [%1];" : "=r"(c) : "l"(&g_cnt) : "memory");
                if (++spins > (1u << 22)) __trap();
            } while (c < NCTA);
            mbar_arrive(BAR(BAR_RSTOK));
        }
        return;
    }

    const int g = lane >> 2, t = lane & 3;
    uint32_t xw[9];
    {
        const uint32_t* xr = (const uint32_t*)(prm.x + warp * DM);
#pragma unroll
        for (int j = 0; j < 9; j++) xw[j] = __ldg(xr + j * 32 + lane);
    }
    const int qb = tid / 18, qq = tid - qb * 18;
    uint2 xres = make_uint2(0, 0);
    if (tid < 144) {
        xres = __ldg((const uint2*)(prm.x + qb * DM + r * 72 + qq * 4));
    }
    layernorm_row<false>(xw);
    DBG_T(18);
    {
        uint32_t* act = (uint32_t*)(smem + SM_R2) + warp * (PITCH / 2);
#pragma unroll
        for (int j = 0; j < 9; j++) act[j * 32 + lane] = xw[j];
    }
    asm volatile("bar.sync 0, 320;" ::: "memory");
    asm volatile("barrier.cluster.arrive.relaxed.aligned;" ::: "memory");
    DBG_T(2);

    {
        const int m = warp & 3, kh = warp >> 2;
        float ca[4] = {0.f, 0.f, 0.f, 0.f}, cb[4] = {0.f, 0.f, 0.f, 0.f};
        const int lrow = (lane & 7) + ((lane >> 4) & 1) * 8;
        const int lchunk = m * 2 + ((lane >> 3) & 1);
        const uint32_t baddr = sb + SM_R2 + (lane & 7) * (PITCH * 2) + (lane >> 3) * 16;
#pragma unroll
        for (int j = 0; j < 5; j++) {
            const int nk = j < 4 ? 4 : 2;
            const int ks0 = j * 8 + kh * nk;
            uint32_t bfr[2][4], afr[4][4];
#pragma unroll
            for (int s = 0; s < nk; s += 2) ldsm_x4(bfr[s / 2][0], bfr[s / 2][1], bfr[s / 2][2], bfr[s / 2][3], baddr + (ks0 + s) * 32);
            mbar_wait(BAR(BAR_FULL + j), 0);
#pragma unroll
            for (int s = 0; s < nk; s++) {
                const int row = (ks0 + s) * 16 + lrow;
                ldsm_x4_t(afr[s][0], afr[s][1], afr[s][2], afr[s][3], sb + row * 128 + ((lchunk ^ (row & 7)) << 4));
            }
#pragma unroll
            for (int s = 0; s < nk; s += 2) {
                mma16816(ca, afr[s][0], afr[s][1], afr[s][2], afr[s][3], bfr[s / 2][0], bfr[s / 2][1]);
                mma16816(cb, afr[s + 1][0], afr[s + 1][1], afr[s + 1][2], afr[s + 1][3], bfr[s / 2][2], bfr[s / 2][3]);
            }
            if (j < 4) {
                cons_sync();
                if (warp < 4 && lane == 0) mbar_arrive(BAR(BAR_EMPTY + j));
            }
        }
        DBG_T(19);
        float* red = (float*)(smem + SM_R1);
        red[(kh * 8 + 2 * t) * 64 + m * 16 + g] = ca[0] + cb[0];
        red[(kh * 8 + 2 * t + 1) * 64 + m * 16 + g] = ca[1] + cb[1];
        red[(kh * 8 + 2 * t) * 64 + m * 16 + g + 8] = ca[2] + cb[2];
        red[(kh * 8 + 2 * t + 1) * 64 + m * 16 + g + 8] = ca[3] + cb[3];
        cons_sync();
        if (warp < 4 && lane == 0) mbar_arrive(BAR(BAR_EMPTY + 4));
        asm volatile("barrier.cluster.wait.acquire.aligned;" ::: "memory");
        if (tid < 64) {
            const int b = tid >> 3, oct = tid & 7;
            const float* p0 = red + b * 64 + oct * 8;
            const float4 u0 = *(const float4*)p0, u1 = *(const float4*)(p0 + 4);
            const float4 v0 = *(const float4*)(p0 + 512), v1 = *(const float4*)(p0 + 516);
            const uint4 w = make_uint4(bf16_pack(u0.x + v0.x, u0.y + v0.y), bf16_pack(u0.z + v0.z, u0.w + v0.w),
                                       bf16_pack(u1.x + v1.x, u1.y + v1.y), bf16_pack(u1.z + v1.z, u1.w + v1.w));
            st_async4(mapa(sb + SM_QS + (r * 64 + oct * 8) * 2, b), w, mapa(BAR(BAR_Q), b));
        }
        mbar_wait_cl(BAR(BAR_Q));
        cons_sync();
    }
    DBG_T(3);

    float4 apart = make_float4(0.f, 0.f, 0.f, 0.f);

#pragma unroll 1
    for (int u = 0; u < 2; u++) {
        {
            uint32_t bq[16];
            {
                const int pi = (g >> 1) & 1, h = g & 1;
#pragma unroll
                for (int j = 0; j < 4; j++) {
                    uint4 v = lds128(sb + SM_QS + (u * 2 + h) * 256 + (4 * (j ^ pi) + t) * 16);
                    if (g >= 4) v = make_uint4(0, 0, 0, 0);
                    bq[4 * j] = v.x; bq[4 * j + 1] = v.y; bq[4 * j + 2] = v.z; bq[4 * j + 3] = v.w;
                }
            }
            const int pig = g & 1;
            const int first = (u ? IT_KB : IT_KA) + (warp >> 2);
            int slot = first % NS; uint32_t ph = (first / NS) & 1;
            const uint32_t rowoff = ((warp & 3) * 16 + g) * 256;
            unsigned short* sc = (unsigned short*)(smem + SM_R1);
            for (int kt = warp >> 2; kt < 32; kt += 2) {
                mbar_wait(BAR(BAR_FULL + slot), ph);
                const uint32_t base = sb + slot * SLOT + rowoff;
                uint4 X[4], Y[4];
#pragma unroll
                for (int j = 0; j < 4; j++) {
                    const uint32_t a = base + (4 * (j ^ pig) + t) * 16;
                    X[j] = lds128(a); Y[j] = lds128(a + 2048);
                }
                float ca[4] = {0.f, 0.f, 0.f, 0.f}, cb[4] = {0.f, 0.f, 0.f, 0.f};
#pragma unroll
                for (int j = 0; j < 4; j++) {
                    mma16816(ca, X[j].x, Y[j].x, X[j].y, Y[j].y, bq[4 * j], bq[4 * j + 1]);
                    mma16816(cb, X[j].z, Y[j].z, X[j].w, Y[j].w, bq[4 * j + 2], bq[4 * j + 3]);
                }
                __syncwarp();
                if (lane == 0) mbar_arrive(BAR(BAR_EMPTY + slot));
                if (t == pig) {
                    const int key = kt * 64 + (warp & 3) * 16 + g;
                    const float scale = 0.08838834764831845f;
                    sc[key] = (unsigned short)bf16_bits(bf16r(ca[0] + cb[0]) * scale);
                    sc[2048 + key] = (unsigned short)bf16_bits(bf16r(ca[1] + cb[1]) * scale);
                    sc[key + 8] = (unsigned short)bf16_bits(bf16r(ca[2] + cb[2]) * scale);
                    sc[2048 + key + 8] = (unsigned short)bf16_bits(bf16r(ca[3] + cb[3]) * scale);
                }
                slot += 2; if (slot >= NS) { slot -= NS; ph ^= 1; }
            }
        }
        cons_sync();
        if (u == 0) DBG_T(4); else DBG_T(7);

        {
            const int h = tid >> 7, idx = tid & 127;
            const uint32_t a = sb + SM_R1 + h * 4096 + idx * 32;
            const uint4 u0 = lds128(a), u1 = lds128(a + 16);
            float e[16];
            e[0] = bf_lo(u0.x); e[1] = bf_hi(u0.x); e[2] = bf_lo(u0.y); e[3] = bf_hi(u0.y);
            e[4] = bf_lo(u0.z); e[5] = bf_hi(u0.z); e[6] = bf_lo(u0.w); e[7] = bf_hi(u0.w);
            e[8] = bf_lo(u1.x); e[9] = bf_hi(u1.x); e[10] = bf_lo(u1.y); e[11] = bf_hi(u1.y);
            e[12] = bf_lo(u1.z); e[13] = bf_hi(u1.z); e[14] = bf_lo(u1.w); e[15] = bf_hi(u1.w);
            float mx = e[0];
#pragma unroll
            for (int i = 1; i < 16; i++) mx = fmaxf(mx, e[i]);
            mx = warp_max(mx);
            float* stat = (float*)(smem + SM_STAT);
            if (lane == 0) stat[warp] = mx;
            cons_sync();
            mx = fmaxf(fmaxf(stat[h * 4], stat[h * 4 + 1]), fmaxf(stat[h * 4 + 2], stat[h * 4 + 3]));
            float sum = 0.f;
#pragma unroll
            for (int i = 0; i < 16; i++) { e[i] = exp2f((e[i] - mx) * 1.4426950408889634f); sum += e[i]; }
            sum = warp_sum(sum);
            if (lane == 0) stat[8 + warp] = sum;
            cons_sync();
            sum = (stat[8 + h * 4] + stat[8 + h * 4 + 1]) + (stat[8 + h * 4 + 2] + stat[8 + h * 4 + 3]);
            const float inv = __fdiv_rn(1.0f, sum);
            uint32_t w[8];
#pragma unroll
            for (int i = 0; i < 8; i++) w[i] = bf16_pack(e[2 * i] * inv, e[2 * i + 1] * inv);
            *(uint4*)(smem + SM_R1 + h * 4096 + idx * 32) = make_uint4(w[0], w[1], w[2], w[3]);
            *(uint4*)(smem + SM_R1 + h * 4096 + idx * 32 + 16) = make_uint4(w[4], w[5], w[6], w[7]);
            cons_sync();
        }
        if (u == 0) DBG_T(5);

        {
            float acc[2][4][4];
#pragma unroll
            for (int a = 0; a < 2; a++)
#pragma unroll
                for (int b = 0; b < 4; b++)
#pragma unroll
                    for (int d = 0; d < 4; d++) acc[a][b][d] = 0.f;
            const int first = (u ? IT_VB : IT_VA) + (warp >> 2);
            const bool bvalid = (g >> 1) == t;
            const uint32_t paddr = sb + SM_R1 + (g & 1) * 4096 + ((warp & 3) * 16 + 4 * t) * 2;
            const uint32_t rowoff = ((warp & 3) * 16 + 4 * t) * 256 + (g ^ (2 * t)) * 16;
            for (int vt = warp >> 2; vt < 32; vt += 2) {
                const int item = first - (warp >> 2) + vt;
                const int slot = item_slot(item);
                const uint2 pbv = lds64(paddr + vt * 128);
                const uint32_t b0 = bvalid ? pbv.x : 0u, b1 = bvalid ? pbv.y : 0u;
                mbar_wait(BAR(BAR_FULL + slot), item_par(item));
                if (u == 1 && vt == TRIG_TILE && tid == 0) mbar_arrive(BAR(BAR_TRIG));
                const uint32_t base = sb + slot * SLOT + rowoff;
                uint4 X[2][4];
#pragma unroll
                for (int hf = 0; hf < 2; hf++)
#pragma unroll
                    for (int i = 0; i < 4; i++) X[hf][i] = lds128(base + i * 256 + hf * 128);
#pragma unroll
                for (int hf = 0; hf < 2; hf++) {
                    const uint32_t x0[4] = {X[hf][0].x, X[hf][0].y, X[hf][0].z, X[hf][0].w};
                    const uint32_t x1[4] = {X[hf][1].x, X[hf][1].y, X[hf][1].z, X[hf][1].w};
                    const uint32_t x2[4] = {X[hf][2].x, X[hf][2].y, X[hf][2].z, X[hf][2].w};
                    const uint32_t x3[4] = {X[hf][3].x, X[hf][3].y, X[hf][3].z, X[hf][3].w};
#pragma unroll
                    for (int m = 0; m < 4; m++) {
                        mma16816(acc[hf][m], __byte_perm(x0[m], x1[m], 0x5410), __byte_perm(x0[m], x1[m], 0x7632),
                                 __byte_perm(x2[m], x3[m], 0x5410), __byte_perm(x2[m], x3[m], 0x7632), b0, b1);
                    }
                }
                __syncwarp();
                if (lane == 0) mbar_arrive(BAR(BAR_EMPTY + slot));
            }
            if (u == 0) DBG_T(6); else DBG_T(8);
            float k1[4][4];
            {
                const bool up = (t & 2) != 0;
#pragma unroll
                for (int m = 0; m < 4; m++)
#pragma unroll
                    for (int d = 0; d < 4; d++) {
                        const float keep = up ? acc[1][m][d] : acc[0][m][d];
                        const float send = up ? acc[0][m][d] : acc[1][m][d];
                        k1[m][d] = keep + __shfl_xor_sync(0xffffffffu, send, 18);
                    }
            }
            float k2[2][4];
            {
                const bool up = (t & 1) != 0;
#pragma unroll
                for (int m = 0; m < 2; m++)
#pragma unroll
                    for (int d = 0; d < 4; d++) {
                        const float keep = up ? k1[2 + m][d] : k1[m][d];
                        const float send = up ? k1[m][d] : k1[2 + m][d];
                        k2[m][d] = keep + __shfl_xor_sync(0xffffffffu, send, 9);
                    }
            }
            float* red = (float*)(smem + SM_R2);
            {
                const int d0 = ((g ^ (2 * t)) + 8 * (t >> 1)) * 8 + (t & 1) * 4;
                *(float4*)(red + warp * 256 + d0) = make_float4(k2[0][0], k2[0][2], k2[1][0], k2[1][2]);
                *(float4*)(red + warp * 256 + 128 + d0) = make_float4(k2[0][1], k2[0][3], k2[1][1], k2[1][3]);
            }
            cons_sync();
            float s = 0.f;
#pragma unroll
            for (int w = 0; w < 8; w++) s += red[w * 256 + tid];
            const uint32_t obuf = sb + SM_R3 + u * (NB * OPITCH * 2);
            const uint32_t obar = BAR(u ? BAR_OB : BAR_OA);
            ((unsigned short*)(smem + SM_OL))[tid] = (unsigned short)bf16_bits(s);
            cons_sync();
            const uint4 ov = lds128(sb + SM_OL + lane * 16);
            st_async4(mapa(obuf + r * (OPITCH * 2) + lane * 16, warp), ov, mapa(obar, warp));
            if (u == 0) {
#pragma unroll
                for (int j = 0; j < 3; j++) mbar_wait(BAR(BAR_FULL + (IT_WOA + j) % NS), ((IT_WOA + j) / NS) & 1);
            } else {
#pragma unroll
                for (int j = 0; j < 3; j++) mbar_wait(BAR(BAR_TW + j), 0);
            }
            const uint32_t wbase = u ? sb + TAIL : sb + (IT_WOA % NS) * SLOT;
            const uint32_t wstride = u ? CHUNK : SLOT;
            uint32_t af[4][3][4];
            gemv_load<4>(af, [&](int k) { return wbase + k * wstride; }, tid);
            mbar_wait_cl(obar);
            if (u == 1) DBG_T(9);
            const float4 p = gemv_mma<4>(af, obuf, OPITCH, (float*)(smem + SM_R2), tid);
            apart.x += p.x; apart.y += p.y; apart.z += p.z; apart.w += p.w;
            if (u == 0) {
                if (warp < 4 && lane == 0) {
#pragma unroll
                    for (int j = 0; j < 3; j++) mbar_arrive(BAR(BAR_EMPTY + (IT_WOA + j) % NS));
                }
                cons_sync();
            }
        }
    }

    uint32_t hw0 = 0, hw1 = 0;
    uint32_t af[9][3][4];
    if (tid < 144) {
        mbar_wait(BAR(BAR_RSTOK), 0);
        st_pub4(&g_scr.ap[r][cl][tid * 4], make_uint4(f2pub(apart.x), f2pub(apart.y), f2pub(apart.z), f2pub(apart.w)));
        DBG_T(10);
    }
    if (tid < 144) {
        { const long long c0 = clock64(); while (clock64() - c0 < POLL_DELAY) { } }
        uint4 v[NCL];
        const uint32_t* ap0 = &g_scr.ap[r][0][tid * 4];
        uint32_t spins = 0;
        while (true) {
#pragma unroll
            for (int c = 0; c < NCL; c++) v[c] = ld_poll4(ap0 + c * 576);
            uint32_t bad = 0;
#pragma unroll
            for (int c = 0; c < NCL; c++)
                bad |= (uint32_t)(v[c].x == SENT) | (uint32_t)(v[c].y == SENT) | (uint32_t)(v[c].z == SENT) | (uint32_t)(v[c].w == SENT);
            if (bad == 0) break;
            if (++spins > (1u << 22)) __trap();
        }
        float s0 = 0.f, s1 = 0.f, s2 = 0.f, s3 = 0.f;
#pragma unroll
        for (int c = 0; c < NCL; c++) {
            s0 += __uint_as_float(v[c].x); s1 += __uint_as_float(v[c].y);
            s2 += __uint_as_float(v[c].z); s3 += __uint_as_float(v[c].w);
        }
        if (tid == 0) mbar_arrive(BAR(BAR_WOFREE));
        DBG_T(25);
        const float h0 = bf16r(bf_lo(xres.x) + bf16r(s0)), h1 = bf16r(bf_hi(xres.x) + bf16r(s1));
        const float h2 = bf16r(bf_lo(xres.y) + bf16r(s2)), h3 = bf16r(bf_hi(xres.y) + bf16r(s3));
        hw0 = bf16_pack(h0, h1); hw1 = bf16_pack(h2, h3);
        if (qb == cl) *(float4*)(smem + SM_HS + qq * 16) = make_float4(h0, h1, h2, h3);
    }
    __syncwarp();
    if (warp < 5) send_slice(hw0, hw1, sb + SM_R1, BAR(BAR_H), r, tid);
    DBG_T(11);
    {
        const int c0 = (9 * (warp & 3)) / 6;
        mbar_wait(BAR(BAR_TW + 3 + c0), 0);
        mbar_wait(BAR(BAR_TW + 3 + c0 + 1), 0);
    }
    DBG_T(27);
    gemv_load<9>(af, [&](int k) { return sb + TAIL_W1 + k * CHUNK; }, tid);
    mbar_wait_cl(BAR(BAR_H));
    DBG_T(20);
    {
        uint32_t* row = (uint32_t*)(smem + SM_R1) + warp * (PITCH / 2);
        uint32_t w[9];
#pragma unroll
        for (int j = 0; j < 9; j++) w[j] = row[j * 32 + lane];
        layernorm_row<true>(w);
#pragma unroll
        for (int j = 0; j < 9; j++) row[j * 32 + lane] = w[j];
    }
    DBG_T(21);
    cons_sync();
    DBG_T(12);

    float4 p = gemv_mma<9>(af, sb + SM_R1, PITCH, (float*)(smem + SM_R2), tid);
    {
        float a = bf16r(p.x), b = bf16r(p.y), c = bf16r(p.z), d = bf16r(p.w);
        a = (a != a) ? a : fmaxf(a, 0.f); b = (b != b) ? b : fmaxf(b, 0.f);
        c = (c != c) ? c : fmaxf(c, 0.f); d = (d != d) ? d : fmaxf(d, 0.f);
        DBG_T(22);
        __syncwarp();
        if (warp < 5) send_slice(bf16_pack(a, b), bf16_pack(c, d), sb + SM_R3, BAR(BAR_H1), r, tid);
        DBG_T(23);
    }
    {
        const int c0 = (9 * (warp & 3)) / 6;
        mbar_wait(BAR(BAR_TW + 9 + c0), 0);
        mbar_wait(BAR(BAR_TW + 9 + c0 + 1), 0);
    }
    gemv_load<9>(af, [&](int k) { return k < 4 ? sb + k * SLOT : sb + TAIL + (k - 4) * CHUNK; }, tid);
    mbar_wait_cl(BAR(BAR_H1));
    DBG_T(13);
    p = gemv_mma<9>(af, sb + SM_R3, PITCH, (float*)(smem + SM_R2), tid);
    {
        if (tid < 144) {
            st_pub4(&g_scr.fp[r][cl][tid * 4], make_uint4(f2pub(p.x), f2pub(p.y), f2pub(p.z), f2pub(p.w)));
            DBG_T(14);
            { const long long c0 = clock64(); while (clock64() - c0 < POLL_DELAY) { } }
            const int quad = tid >> 3, c = tid & 7;
            uint4 w;
            uint32_t spins = 0;
            while (true) {
                w = ld_poll4(&g_scr.fp[r][c][cl * 72 + quad * 4]);
                if (vec_valid(w)) break;
                if (++spins > (1u << 22)) __trap();
            }
            apart = make_float4(__uint_as_float(w.x), __uint_as_float(w.y), __uint_as_float(w.z), __uint_as_float(w.w));
        } else {
            apart = make_float4(0.f, 0.f, 0.f, 0.f);
        }
        if (warp < 5) {
            __syncwarp();
#pragma unroll
            for (int o = 1; o < 8; o <<= 1) {
                apart.x += __shfl_xor_sync(0xffffffffu, apart.x, o); apart.y += __shfl_xor_sync(0xffffffffu, apart.y, o);
                apart.z += __shfl_xor_sync(0xffffffffu, apart.z, o); apart.w += __shfl_xor_sync(0xffffffffu, apart.w, o);
            }
            if (tid < 144 && (tid & 7) == 0) {
                const int quad = tid >> 3;
                const float4 h = *(const float4*)(smem + SM_HS + quad * 16);
                uint2 o;
                o.x = bf16_pack(h.x + bf16r(apart.x), h.y + bf16r(apart.y));
                o.y = bf16_pack(h.z + bf16r(apart.z), h.w + bf16r(apart.w));
                *(uint2*)(prm.out + cl * DM + r * 72 + quad * 4) = o;
            }
            if (blockIdx.x == 0 && tid == 0) g_cnt = 0;
            DBG_T(15);
        }
    }
}

typedef CUresult (*EncodeTiledFn)(CUtensorMap*, CUtensorMapDataType, cuuint32_t, void*, const cuuint64_t*, const cuuint64_t*,
                                  const cuuint32_t*, const cuuint32_t*, CUtensorMapInterleave, CUtensorMapSwizzle,
                                  CUtensorMapL2promotion, CUtensorMapFloatOOBfill);

void make_map(EncodeTiledFn fn, CUtensorMap* m, const void* ptr, uint64_t cols, uint64_t rows, uint32_t bc, uint32_t br,
              CUtensorMapSwizzle sw) {
    cuuint64_t dims[2] = {cols, rows};
    cuuint64_t strides[1] = {cols * 2};
    cuuint32_t box[2] = {bc, br};
    cuuint32_t es[2] = {1, 1};
    fn(m, CU_TENSOR_MAP_DATA_TYPE_BFLOAT16, 2, const_cast<void*>(ptr), dims, strides, box, es, CU_TENSOR_MAP_INTERLEAVE_NONE, sw,
       CU_TENSOR_MAP_L2_PROMOTION_L2_256B, CU_TENSOR_MAP_FLOAT_OOB_FILL_NONE);
}

}

extern "C" void kernel_launch(void* const* d_in, const int* in_sizes, int n_in, void* d_out, int out_size) {
    (void)in_sizes; (void)n_in; (void)out_size;
    static EncodeTiledFn enc = nullptr;
    if (!enc) {
        void* fn = nullptr;
        cudaDriverEntryPointQueryResult qr;
        cudaGetDriverEntryPoint("cuTensorMapEncodeTiled", &fn, cudaEnableDefault, &qr);
        enc = (EncodeTiledFn)fn;
        cudaFuncSetAttribute(fused_decode_kernel, cudaFuncAttributeMaxDynamicSharedMemorySize, SM_TOTAL);
    }
    CUtensorMap mq, mo, m1, m2;
    make_map(enc, &mq, d_in[3], 4096, DM, 64, 128, CU_TENSOR_MAP_SWIZZLE_128B);
    make_map(enc, &mo, d_in[4], DM, 4096, 72, 32, CU_TENSOR_MAP_SWIZZLE_NONE);
    make_map(enc, &m1, d_in[6], DFF, DM, 72, 96, CU_TENSOR_MAP_SWIZZLE_NONE);
    make_map(enc, &m2, d_in[7], DM, DFF, 72, 96, CU_TENSOR_MAP_SWIZZLE_NONE);
    Params p;
    p.x = (const __nv_bfloat16*)d_in[0];
    p.k = (const __nv_bfloat16*)d_in[1];
    p.v = (const __nv_bfloat16*)d_in[2];
    p.out = (__nv_bfloat16*)d_out;
    fused_decode_kernel<<<NCTA, 320, SM_TOTAL, cudaStreamPerThread>>>(mq, mo, m1, m2, p);
}
```

```cpp
#include <cuda_runtime.h>
#include <cuda_bf16.h>
#include <cuda.h>
#include <stdint.h>

namespace {

constexpr int NB = 8;
constexpr int DM = 576;
constexpr int HKV = 16;
constexpr int DH = 128;
constexpr int SK = 8192;
constexpr int WIN = 2048;
constexpr int DFF = 4608;
constexpr int NCL = 8;
constexpr int CS = 8;
constexpr int NCTA = NCL * CS;

constexpr int SLOT = 16384;
constexpr int NS = 12;
constexpr int IT_KA = 5, IT_VA = 37, IT_WOA = 69, IT_KB = 72, IT_VB = 104, IT_FIFO_END = 128;
constexpr int CHUNK = 96 * 144;
constexpr int TAIL = 4 * SLOT;
constexpr int TAIL_W1 = TAIL + 256 * 144;

#define POLL_DELAY 300
#define TRIG_TILE 8
#define BURST 6
#define KFIRST 0
#define INFLIGHT 10

constexpr int PITCH = 584;
constexpr int OPITCH = 264;
constexpr int SM_R1 = NS * SLOT;
constexpr int SM_R2 = SM_R1 + NB * PITCH * 2;
constexpr int SM_R3 = SM_R2 + NB * PITCH * 2;
constexpr int SM_QS = SM_R3 + NB * PITCH * 2;
constexpr int SM_HS = SM_QS + 1024;
constexpr int SM_OL = SM_HS + 288;
constexpr int SM_STAT = SM_OL + 512;
constexpr int SM_BAR = SM_STAT + 96;
constexpr int BAR_FULL = 0, BAR_EMPTY = 12, BAR_TW = 24, BAR_Q = 39, BAR_OA = 40, BAR_OB = 41, BAR_H = 42, BAR_H1 = 43,
              BAR_WOFREE = 44, BAR_TRIG = 45, BAR_RSTOK = 46, NBAR = 47;
constexpr int SM_DBG = SM_BAR + NBAR * 8;
constexpr int SM_TOTAL = SM_DBG + 32 * 8;
static_assert(SM_TOTAL <= 232448, "smem");
static_assert(2 * NB * OPITCH * 2 <= NB * PITCH * 2, "o_all");

constexpr uint32_t SENT = 0xffffffffu;

struct Scratch {
    uint32_t ap[CS][NCL][576];
    uint32_t fp[CS][NCL][576];
};
__device__ __align__(128) Scratch g_scr;
__device__ uint32_t g_cnt;

#define DBG_T(i) do { } while (0)

__device__ __forceinline__ uint32_t smem_u32(const void* p) { return (uint32_t)__cvta_generic_to_shared(p); }
__device__ __forceinline__ void mbar_init(uint32_t bar, uint32_t cnt) {
    asm volatile("mbarrier.init.shared::cta.b64 [%0], %1;" ::"r"(bar), "r"(cnt) : "memory");
}
__device__ __forceinline__ void mbar_expect_tx(uint32_t bar, uint32_t bytes) {
    asm volatile("mbarrier.arrive.expect_tx.shared::cta.b64 _, [%0], %1;" ::"r"(bar), "r"(bytes) : "memory");
}
__device__ __forceinline__ void mbar_arrive(uint32_t bar) {
    asm volatile("mbarrier.arrive.shared::cta.b64 _, [%0];" ::"r"(bar) : "memory");
}
__device__ __forceinline__ bool mbar_try(uint32_t bar, uint32_t parity) {
    uint32_t ok;
    asm volatile("{\n.reg .pred p;\nmbarrier.try_wait.parity.shared::cta.b64 p, [%1], %2;\nselp.u32 %0, 1, 0, p;\n}"
                 : "=r"(ok) : "r"(bar), "r"(parity) : "memory");
    return ok != 0;
}
__device__ __forceinline__ void mbar_wait(uint32_t bar, uint32_t parity) {
    uint32_t spins = 0;
    while (!mbar_try(bar, parity)) {
        if (++spins > (1u << 22)) __trap();
    }
}
__device__ __forceinline__ bool mbar_try_cl(uint32_t bar, uint32_t parity) {
    uint32_t ok;
    asm volatile("{\n.reg .pred p;\nmbarrier.try_wait.parity.acquire.cluster.shared::cta.b64 p, [%1], %2;\nselp.u32 %0, 1, 0, p;\n}"
                 : "=r"(ok) : "r"(bar), "r"(parity) : "memory");
    return ok != 0;
}
__device__ __forceinline__ void mbar_wait_cl(uint32_t bar) {
    uint32_t spins = 0;
    while (!mbar_try_cl(bar, 0)) {
        if (++spins > (1u << 22)) __trap();
    }
}
__device__ __forceinline__ void bulk_g2s(uint32_t dst, const void* src, uint32_t bytes, uint32_t bar, uint64_t pol) {
    asm volatile("cp.async.bulk.shared::cluster.global.mbarrier::complete_tx::bytes.L2::cache_hint [%0], [%1], %2, [%3], %4;"
                 ::"r"(dst), "l"(src), "r"(bytes), "r"(bar), "l"(pol) : "memory");
}
__device__ __forceinline__ void tma_2d(uint32_t dst, const CUtensorMap* map, int x, int y, uint32_t bar, uint64_t pol) {
    asm volatile("cp.async.bulk.tensor.2d.shared::cluster.global.mbarrier::complete_tx::bytes.L2::cache_hint [%0], [%1, {%3, %4}], [%2], %5;"
                 ::"r"(dst), "l"(map), "r"(bar), "r"(x), "r"(y), "l"(pol) : "memory");
}
__device__ __forceinline__ void cons_sync() { asm volatile("bar.sync 1, 256;" ::: "memory"); }
__device__ __forceinline__ uint32_t mapa(uint32_t a, uint32_t rank) {
    uint32_t r; asm("mapa.shared::cluster.u32 %0, %1, %2;" : "=r"(r) : "r"(a), "r"(rank)); return r;
}
__device__ __forceinline__ void st_async4(uint32_t addr, uint4 v, uint32_t bar) {
    asm volatile("st.async.weak.shared::cluster.mbarrier::complete_tx::bytes.v4.b32 [%0], {%1,%2,%3,%4}, [%5];"
                 ::"r"(addr), "r"(v.x), "r"(v.y), "r"(v.z), "r"(v.w), "r"(bar) : "memory");
}
__device__ __forceinline__ uint4 lds128(uint32_t a) {
    uint4 v; asm volatile("ld.shared.v4.u32 {%0,%1,%2,%3}, [%4];" : "=r"(v.x), "=r"(v.y), "=r"(v.z), "=r"(v.w) : "r"(a)); return v;
}
__device__ __forceinline__ uint2 lds64(uint32_t a) {
    uint2 v; asm volatile("ld.shared.v2.u32 {%0,%1}, [%2];" : "=r"(v.x), "=r"(v.y) : "r"(a)); return v;
}
__device__ __forceinline__ void ldsm_x4(uint32_t& r0, uint32_t& r1, uint32_t& r2, uint32_t& r3, uint32_t a) {
    asm volatile("ldmatrix.sync.aligned.m8n8.x4.shared.b16 {%0,%1,%2,%3}, [%4];"
                 : "=r"(r0), "=r"(r1), "=r"(r2), "=r"(r3) : "r"(a));
}
__device__ __forceinline__ void ldsm_x2(uint32_t& r0, uint32_t& r1, uint32_t a) {
    asm volatile("ldmatrix.sync.aligned.m8n8.x2.shared.b16 {%0,%1}, [%2];" : "=r"(r0), "=r"(r1) : "r"(a));
}
__device__ __forceinline__ void ldsm_x4_t(uint32_t& r0, uint32_t& r1, uint32_t& r2, uint32_t& r3, uint32_t a) {
    asm volatile("ldmatrix.sync.aligned.m8n8.x4.trans.shared.b16 {%0,%1,%2,%3}, [%4];"
                 : "=r"(r0), "=r"(r1), "=r"(r2), "=r"(r3) : "r"(a));
}
__device__ __forceinline__ void mma16816(float (&c)[4], uint32_t a0, uint32_t a1, uint32_t a2, uint32_t a3, uint32_t b0, uint32_t b1) {
    asm volatile("mma.sync.aligned.m16n8k16.row.col.f32.bf16.bf16.f32 {%0,%1,%2,%3}, {%4,%5,%6,%7}, {%8,%9}, {%0,%1,%2,%3};"
                 : "+f"(c[0]), "+f"(c[1]), "+f"(c[2]), "+f"(c[3])
                 : "r"(a0), "r"(a1), "r"(a2), "r"(a3), "r"(b0), "r"(b1));
}
__device__ __forceinline__ uint4 ld_poll4(const uint32_t* p) {
    uint4 v;
    asm volatile("ld.relaxed.gpu.global.v4.u32 {%0,%1,%2,%3}, [%4];" : "=r"(v.x), "=r"(v.y), "=r"(v.z), "=r"(v.w) : "l"(p) : "memory");
    return v;
}
__device__ __forceinline__ void st_pub4(uint32_t* p, uint4 v) {
    asm volatile("st.relaxed.gpu.global.v4.u32 [%0], {%1,%2,%3,%4};" ::"l"(p), "r"(v.x), "r"(v.y), "r"(v.z), "r"(v.w) : "memory");
}
__device__ __forceinline__ bool vec_valid(const uint4& v) { return v.x != SENT && v.y != SENT && v.z != SENT && v.w != SENT; }
__device__ __forceinline__ uint32_t f2pub(float f) { uint32_t u = __float_as_uint(f); return u == SENT ? 0x7fffffffu : u; }

__device__ __forceinline__ uint32_t bf16_pack(float lo, float hi) {
    uint32_t r; asm("cvt.rn.bf16x2.f32 %0, %1, %2;" : "=r"(r) : "f"(hi), "f"(lo)); return r;
}
__device__ __forceinline__ uint32_t bf16_bits(float f) { return bf16_pack(f, 0.f); }
__device__ __forceinline__ float bf16r(float f) { return __uint_as_float(bf16_pack(0.f, f)); }
__device__ __forceinline__ float bf_lo(uint32_t w) { return __uint_as_float(w << 16); }
__device__ __forceinline__ float bf_hi(uint32_t w) { return __uint_as_float(w & 0xffff0000u); }
__device__ __forceinline__ float warp_sum(float v) {
#pragma unroll
    for (int o = 16; o > 0; o >>= 1) v += __shfl_xor_sync(0xffffffffu, v, o);
    return v;
}
__device__ __forceinline__ float warp_max(float v) {
#pragma unroll
    for (int o = 16; o > 0; o >>= 1) v = fmaxf(v, __shfl_xor_sync(0xffffffffu, v, o));
    return v;
}

template <bool FAST>
__device__ __forceinline__ void layernorm_row(uint32_t (&w)[9]) {
    const float x0 = __shfl_sync(0xffffffffu, bf_lo(w[0]), 0);
    float s0 = 0.f, s1 = 0.f, s2 = 0.f, q0 = 0.f, q1 = 0.f, q2 = 0.f;
#pragma unroll
    for (int j = 0; j < 3; j++) {
        const float a0 = bf_lo(w[j]) - x0, a1 = bf_hi(w[j]) - x0;
        const float b0 = bf_lo(w[3 + j]) - x0, b1 = bf_hi(w[3 + j]) - x0;
        const float c0 = bf_lo(w[6 + j]) - x0, c1 = bf_hi(w[6 + j]) - x0;
        s0 += a0 + a1; s1 += b0 + b1; s2 += c0 + c1;
        q0 = fmaf(a0, a0, fmaf(a1, a1, q0)); q1 = fmaf(b0, b0, fmaf(b1, b1, q1)); q2 = fmaf(c0, c0, fmaf(c1, c1, q2));
    }
    float s = (s0 + s1) + s2, q = (q0 + q1) + q2;
#pragma unroll
    for (int o = 16; o > 0; o >>= 1) { s += __shfl_xor_sync(0xffffffffu, s, o); q += __shfl_xor_sync(0xffffffffu, q, o); }
    const float md = s * (1.0f / 576.0f);
    const float m_b = bf16r(x0 + md);
    const float var_b = bf16r(fmaxf(q * (1.0f / 576.0f) - md * md, 0.f));
    float sq, inv;
    if (FAST) asm("sqrt.approx.f32 %0, %1;" : "=f"(sq) : "f"(bf16r(var_b + 1e-5f)));
    else sq = __fsqrt_rn(bf16r(var_b + 1e-5f));
    const float sd = bf16r(sq);
    if (FAST) asm("rcp.approx.f32 %0, %1;" : "=f"(inv) : "f"(sd));
    else inv = __frcp_rn(sd);
#pragma unroll
    for (int j = 0; j < 9; j++) {
        const uint32_t c = bf16_pack(bf_lo(w[j]) - m_b, bf_hi(w[j]) - m_b);
        w[j] = bf16_pack(bf_lo(c) * inv, bf_hi(c) * inv);
    }
}

__device__ __forceinline__ int item_slot(int i) { return i < IT_FIFO_END ? i % NS : (i - IT_FIFO_END) & 3; }
__device__ __forceinline__ uint32_t item_par(int i) { return i < IT_FIFO_END ? (i / NS) & 1 : (i < IT_FIFO_END + 4 ? 1u : 0u); }

template <int KQ, int NT, typename ChunkAddr>
__device__ __forceinline__ void gemv_load_t(uint32_t (&af)[KQ][3][4], ChunkAddr chunk_addr, int tid) {
    const int warp = tid >> 5, lane = tid & 31;
    const int kq = warp & 3, mg = warp >> 2;
    const int lrow = (lane & 7) + ((lane >> 4) & 1) * 8;
    const int lcol = ((lane >> 3) & 1) * 16;
#pragma unroll
    for (int s = 0; s < KQ; s++) {
        const int ks = kq * KQ + s;
        const uint32_t a = chunk_addr(ks / 6) + ((ks % 6) * 16 + lrow) * 144 + lcol + mg * 96;
#pragma unroll
        for (int m = 0; m < NT; m++) ldsm_x4_t(af[s][m][0], af[s][m][1], af[s][m][2], af[s][m][3], a + m * 32);
    }
}
template <int KQ, typename ChunkAddr>
__device__ __forceinline__ void gemv_load(uint32_t (&af)[KQ][3][4], ChunkAddr chunk_addr, int tid) {
    if (tid < 128) gemv_load_t<KQ, 3>(af, chunk_addr, tid);
    else gemv_load_t<KQ, 2>(af, chunk_addr, tid);
}
template <int KQ, int NT>
__device__ __forceinline__ void gemv_mma_t(const uint32_t (&af)[KQ][3][4], uint32_t act, int apitch, float* red, int tid) {
    const int warp = tid >> 5, lane = tid & 31, g = lane >> 2, t = lane & 3;
    const int kq = warp & 3, mg = warp >> 2;
    float acc[NT][4], acd[NT][4];
#pragma unroll
    for (int m = 0; m < NT; m++) {
        acc[m][0] = acc[m][1] = acc[m][2] = acc[m][3] = 0.f;
        acd[m][0] = acd[m][1] = acd[m][2] = acd[m][3] = 0.f;
    }
    const uint32_t baddr = act + (lane & 7) * (apitch * 2) + (lane >> 3) * 16 + kq * KQ * 32;
    uint32_t bf[KQ + 1][2];
#pragma unroll
    for (int s = 0; s + 1 < KQ; s += 2) ldsm_x4(bf[s][0], bf[s][1], bf[s + 1][0], bf[s + 1][1], baddr + s * 32);
    if (KQ & 1) ldsm_x2(bf[KQ - 1][0], bf[KQ - 1][1], act + (lane & 7) * (apitch * 2) + ((lane >> 3) & 1) * 16 + (kq * KQ + KQ - 1) * 32);
#pragma unroll
    for (int s = 0; s < KQ; s++) {
#pragma unroll
        for (int m = 0; m < NT; m++) {
            if (s & 1) mma16816(acd[m], af[s][m][0], af[s][m][1], af[s][m][2], af[s][m][3], bf[s][0], bf[s][1]);
            else mma16816(acc[m], af[s][m][0], af[s][m][1], af[s][m][2], af[s][m][3], bf[s][0], bf[s][1]);
        }
    }
    float* rp = red + kq * 576;
#pragma unroll
    for (int m = 0; m < NT; m++) {
        const int col = mg * 48 + m * 16 + g;
        rp[(2 * t) * 72 + col] = acc[m][0] + acd[m][0];
        rp[(2 * t + 1) * 72 + col] = acc[m][1] + acd[m][1];
        if (NT == 3 || m == 0) {
            rp[(2 * t) * 72 + col + 8] = acc[m][2] + acd[m][2];
            rp[(2 * t + 1) * 72 + col + 8] = acc[m][3] + acd[m][3];
        }
    }
}
__device__ __forceinline__ int il_step(int kq, int s) {
    const int base = 12 * (s / 3), i = s % 3;
    if (kq < 2) return base + (i < 2 ? 2 * kq + i : 6 + kq);
    return base + (i == 0 ? 2 + kq : 4 + 2 * kq + i - 1);
}
template <int NT, typename ChunkAddr, typename ChunkWait, typename ActWait>
__device__ __forceinline__ void gemv_w2_t(uint32_t (&af)[9][3][4], ChunkAddr chunk_addr, ChunkWait chunk_wait, ActWait act_wait,
                                          uint32_t act, int apitch, float* red, int tid) {
    const int warp = tid >> 5, lane = tid & 31, g = lane >> 2, t = lane & 3;
    const int kq = warp & 3, mg = warp >> 2;
    const int lrow = (lane & 7) + ((lane >> 4) & 1) * 8;
    const int lcol = ((lane >> 3) & 1) * 16;
    auto load = [&](int s) {
        const int ks = il_step(kq, s);
        if (s % 3 != 1) chunk_wait(2 * (s / 3) + ((s % 3) == 2));
        else if (kq >= 2) chunk_wait(2 * (s / 3) + 1);
        const uint32_t a = chunk_addr(ks / 6) + ((ks % 6) * 16 + lrow) * 144 + lcol + mg * 96;
#pragma unroll
        for (int m = 0; m < NT; m++) ldsm_x4_t(af[s][m][0], af[s][m][1], af[s][m][2], af[s][m][3], a + m * 32);
    };
#pragma unroll
    for (int s = 0; s < 6; s++) load(s);
    act_wait();
    float acc[NT][4], acd[NT][4];
#pragma unroll
    for (int m = 0; m < NT; m++) {
        acc[m][0] = acc[m][1] = acc[m][2] = acc[m][3] = 0.f;
        acd[m][0] = acd[m][1] = acd[m][2] = acd[m][3] = 0.f;
    }
    const uint32_t baddr = act + (lane & 7) * (apitch * 2) + ((lane >> 3) & 1) * 16;
    uint32_t bf[9][2];
#pragma unroll
    for (int s = 0; s < 9; s++) ldsm_x2(bf[s][0], bf[s][1], baddr + il_step(kq, s) * 32);
#pragma unroll
    for (int s = 0; s < 6; s++) {
#pragma unroll
        for (int m = 0; m < NT; m++) {
            if (s & 1) mma16816(acd[m], af[s][m][0], af[s][m][1], af[s][m][2], af[s][m][3], bf[s][0], bf[s][1]);
            else mma16816(acc[m], af[s][m][0], af[s][m][1], af[s][m][2], af[s][m][3], bf[s][0], bf[s][1]);
        }
    }
#pragma unroll
    for (int s = 6; s < 9; s++) load(s);
#pragma unroll
    for (int s = 6; s < 9; s++) {
#pragma unroll
        for (int m = 0; m < NT; m++) {
            if (s & 1) mma16816(acd[m], af[s][m][0], af[s][m][1], af[s][m][2], af[s][m][3], bf[s][0], bf[s][1]);
            else mma16816(acc[m], af[s][m][0], af[s][m][1], af[s][m][2], af[s][m][3], bf[s][0], bf[s][1]);
        }
    }
    float* rp = red + kq * 576;
#pragma unroll
    for (int m = 0; m < NT; m++) {
        const int col = mg * 48 + m * 16 + g;
        rp[(2 * t) * 72 + col] = acc[m][0] + acd[m][0];
        rp[(2 * t + 1) * 72 + col] = acc[m][1] + acd[m][1];
        if (NT == 3 || m == 0) {
            rp[(2 * t) * 72 + col + 8] = acc[m][2] + acd[m][2];
            rp[(2 * t + 1) * 72 + col + 8] = acc[m][3] + acd[m][3];
        }
    }
}
template <int KQ>
__device__ __forceinline__ float4 gemv_mma(const uint32_t (&af)[KQ][3][4], uint32_t act, int apitch, float* red, int tid) {
    if (tid < 128) gemv_mma_t<KQ, 3>(af, act, apitch, red, tid);
    else gemv_mma_t<KQ, 2>(af, act, apitch, red, tid);
    cons_sync();
    float4 o = make_float4(0.f, 0.f, 0.f, 0.f);
    if (tid < 144) {
        const float4 p0 = *(const float4*)(red + tid * 4), p1 = *(const float4*)(red + 576 + tid * 4);
        const float4 p2 = *(const float4*)(red + 1152 + tid * 4), p3 = *(const float4*)(red + 1728 + tid * 4);
        o.x = (p0.x + p1.x) + (p2.x + p3.x); o.y = (p0.y + p1.y) + (p2.y + p3.y);
        o.z = (p0.z + p1.z) + (p2.z + p3.z); o.w = (p0.w + p1.w) + (p2.w + p3.w);
    }
    return o;
}

__device__ __forceinline__ void send_slice(uint32_t w0, uint32_t w1, uint32_t buf, uint32_t bar, int rank, int tid) {
    const uint32_t n0 = __shfl_xor_sync(0xffffffffu, w0, 1), n1 = __shfl_xor_sync(0xffffffffu, w1, 1);
    if (tid < 144) {
        const int b = tid / 18, quad = tid - b * 18, odd = quad & 1;
        const uint4 v = odd ? make_uint4(n0, n1, w0, w1) : make_uint4(w0, w1, n0, n1);
        const uint32_t a = buf + (b * PITCH + rank * 72 + (quad & ~1) * 4) * 2;
#pragma unroll
        for (int d = 0; d < 4; d++) {
            const int dest = odd * 4 + d;
            st_async4(mapa(a, dest), v, mapa(bar, dest));
        }
    }
}

struct Params {
    const __nv_bfloat16* x;
    const __nv_bfloat16* k;
    const __nv_bfloat16* v;
    __nv_bfloat16* out;
};

__global__ void __cluster_dims__(CS, 1, 1) __launch_bounds__(320, 1)
fused_decode_kernel(const __grid_constant__ CUtensorMap map_wq, const __grid_constant__ CUtensorMap map_wo,
                    const __grid_constant__ CUtensorMap map_w1, const __grid_constant__ CUtensorMap map_w2,
                    const Params prm)
{
    extern __shared__ __align__(1024) unsigned char smem[];
    const uint32_t sb = smem_u32(smem);
    const int tid = threadIdx.x, warp = tid >> 5, lane = tid & 31;
    const int cl = blockIdx.x >> 3;
    const int r = blockIdx.x & 7;
    const uint32_t bars = sb + SM_BAR;
    auto BAR = [&](int i) -> uint32_t { return bars + i * 8; };

    constexpr uint64_t pol = 0x12F0000000000000ull;
    int tid_op;
    asm volatile("mov.u32 %0, %1;" : "=r"(tid_op) : "r"(tid));
    if (tid_op == 256) {
        DBG_T(0);
#pragma unroll
        for (int k = 0; k < BURST; k++) mbar_init(BAR(BAR_FULL + k), 1);
        asm volatile("fence.mbarrier_init.release.cluster;" ::: "memory");
        const char* k0 = (const char*)prm.k + ((size_t)(r * HKV + 2 * cl) * SK + (SK - WIN)) * (DH * 2);
#pragma unroll
        for (int k = IT_KA; k < IT_KA + KFIRST; k++) {
            mbar_expect_tx(BAR(BAR_FULL + k), SLOT);
            bulk_g2s(sb + k * SLOT, k0 + (size_t)(k - IT_KA) * SLOT, SLOT, BAR(BAR_FULL + k), pol);
        }
#pragma unroll
        for (int k = 0; k < IT_KA; k++) {
            mbar_expect_tx(BAR(BAR_FULL + k), SLOT);
            tma_2d(sb + k * SLOT, &map_wq, cl * 512 + r * 64, k * 128, BAR(BAR_FULL + k), pol);
        }
#pragma unroll
        for (int k = IT_KA + KFIRST; k < BURST; k++) {
            mbar_expect_tx(BAR(BAR_FULL + k), SLOT);
            bulk_g2s(sb + k * SLOT, k0 + (size_t)(k - IT_KA) * SLOT, SLOT, BAR(BAR_FULL + k), pol);
        }
        DBG_T(16);
    } else if (tid_op == 288) {
#pragma unroll 1
        for (int k = BAR_FULL + BURST; k < NBAR; k++) mbar_init(BAR(k), (k >= BAR_EMPTY && k < BAR_TW) ? 4 : 1);
        mbar_expect_tx(BAR(BAR_Q), CS * 128);
        mbar_expect_tx(BAR(BAR_OA), CS * 512);
        mbar_expect_tx(BAR(BAR_OB), CS * 512);
        mbar_expect_tx(BAR(BAR_H), CS * 1152);
        mbar_expect_tx(BAR(BAR_H1), CS * 1152);
        asm volatile("fence.mbarrier_init.release.cluster;" ::: "memory");
    }
    __syncwarp();
    if ((tid_op >> 5) == 9) asm volatile("bar.arrive 0, 320;" ::: "memory");
    if (warp == 8) {
        const char* kv[2][2];
#pragma unroll
        for (int u = 0; u < 2; u++) {
            const size_t off = ((size_t)(r * HKV + 2 * cl + u) * SK + (SK - WIN)) * (DH * 2);
            kv[u][0] = (const char*)prm.k + off;
            kv[u][1] = (const char*)prm.v + off;
        }
        auto issue_fifo = [&](int i) {
            const int slot = item_slot(i);
            const uint32_t dst = sb + slot * SLOT, fb = BAR(BAR_FULL + slot);
            if (i < IT_KA) {
                mbar_expect_tx(fb, SLOT);
                tma_2d(dst, &map_wq, cl * 512 + r * 64, i * 128, fb, pol);
            } else if (i >= IT_WOA && i < IT_KB) {
                const int j = i - IT_WOA, nb = j < 2 ? 3 : 2;
                mbar_expect_tx(fb, nb * 32 * 144);
                for (int u = 0; u < nb; u++) tma_2d(dst + u * 32 * 144, &map_wo, r * 72, cl * 512 + j * 96 + u * 32, fb, pol);
            } else {
                const char* src = i < IT_VA ? kv[0][0] + (size_t)(i - IT_KA) * SLOT
                                : i < IT_WOA ? kv[0][1] + (size_t)(i - IT_VA) * SLOT
                                : i < IT_VB ? kv[1][0] + (size_t)(i - IT_KB) * SLOT
                                            : kv[1][1] + (size_t)(i - IT_VB) * SLOT;
                mbar_expect_tx(fb, SLOT);
                bulk_g2s(dst, src, SLOT, fb, pol);
            }
        };
        int i = BURST;
        asm volatile("bar.sync 0, 320;" ::: "memory");
        asm volatile("barrier.cluster.arrive.relaxed.aligned;" ::: "memory");
        if (lane == 0) {
            for (; i < IT_FIFO_END; i++) {
                if (i >= NS) mbar_wait(BAR(BAR_EMPTY + i % NS), ((i / NS) - 1) & 1);
                if (i >= INFLIGHT) mbar_wait(BAR(BAR_FULL + (i - INFLIGHT) % NS), ((i - INFLIGHT) / NS) & 1);
                issue_fifo(i);
            }
            auto issue_w1 = [&](int k) {
                mbar_expect_tx(BAR(BAR_TW + 3 + k), CHUNK);
                tma_2d(sb + TAIL_W1 + k * CHUNK, &map_w1, cl * 576 + r * 72, k * 96, BAR(BAR_TW + 3 + k), pol);
            };
            auto issue_wob = [&](int j) {
                const int nb = j < 2 ? 3 : 2;
                mbar_expect_tx(BAR(BAR_TW + j), nb * 32 * 144);
                for (int u = 0; u < nb; u++)
                    tma_2d(sb + TAIL + j * CHUNK + u * 32 * 144, &map_wo, r * 72, cl * 512 + 256 + j * 96 + u * 32, BAR(BAR_TW + j), pol);
            };
            auto issue_w2 = [&](int k, uint32_t dst) {
                mbar_expect_tx(BAR(BAR_TW + 9 + k), CHUNK);
                tma_2d(dst, &map_w2, r * 72, cl * 576 + k * 96, BAR(BAR_TW + 9 + k), pol);
            };
            mbar_wait(BAR(BAR_EMPTY + 8), 1); mbar_wait(BAR(BAR_EMPTY + 9), 1);
            mbar_wait(BAR(BAR_EMPTY + 10), 1); mbar_wait(BAR(BAR_EMPTY + 11), 1);
            for (int k = 0; k < 4; k++) { mbar_wait(BAR(BAR_EMPTY + k), 0); issue_fifo(IT_FIFO_END + k); }
            mbar_wait(BAR(BAR_EMPTY + 4), 0); issue_wob(0);
            mbar_wait(BAR(BAR_EMPTY + 5), 0); issue_wob(1);
            mbar_wait(BAR(BAR_EMPTY + 6), 0); issue_wob(2);
            mbar_wait(BAR(BAR_EMPTY + 7), 0);
            for (int k = 0; k < 4; k++) { mbar_wait(BAR(BAR_EMPTY + k), 1); issue_fifo(IT_FIFO_END + 4 + k); }
            mbar_wait(BAR(BAR_FULL + 3), 0);
            for (int k = 0; k < 6; k++) issue_w1(k);
            mbar_wait(BAR(BAR_TW + 3 + 5), 0);
            for (int k = 0; k < 4; k++) { mbar_wait(BAR(BAR_EMPTY + k), 0); issue_w2(k, sb + k * SLOT); }
            mbar_wait(BAR(BAR_WOFREE), 0);
            issue_w2(4, sb + TAIL); issue_w2(5, sb + TAIL + CHUNK);
            DBG_T(1);
        }
        return;
    }

    if (warp == 9) {
        asm volatile("barrier.cluster.arrive.relaxed.aligned;" ::: "memory");
        if (lane >= 1 && lane < 4) {
            const CUtensorMap* mp = lane == 1 ? &map_wo : lane == 2 ? &map_w1 : &map_w2;
            asm volatile("prefetch.tensormap [%0];" ::"l"(mp) : "memory");
        }
        mbar_wait(BAR(BAR_TRIG), 0);
        for (int i = lane; i < 144; i += 32) {
            st_pub4(&g_scr.ap[r][cl][i * 4], make_uint4(SENT, SENT, SENT, SENT));
            st_pub4(&g_scr.fp[r][cl][i * 4], make_uint4(SENT, SENT, SENT, SENT));
        }
        __threadfence();
        __syncwarp();
        if (lane == 0) {
            __threadfence();
            asm volatile("red.relaxed.gpu.global.add.u32 [%0], 1;" ::"l"(&g_cnt) : "memory");
            uint32_t c, spins = 0;
            do {
                asm volatile("ld.acquire.gpu.global.u32 %0, [%1];" : "=r"(c) : "l"(&g_cnt) : "memory");
                if (++spins > (1u << 22)) __trap();
            } while (c < NCTA);
            mbar_arrive(BAR(BAR_RSTOK));
        }
        return;
    }

    const int g = lane >> 2, t = lane & 3;
    uint32_t xw[9];
    {
        const uint32_t* xr = (const uint32_t*)(prm.x + warp * DM);
#pragma unroll
        for (int j = 0; j < 9; j++) xw[j] = __ldg(xr + j * 32 + lane);
    }
    const int qb = tid / 18, qq = tid - qb * 18;
    uint2 xres = make_uint2(0, 0);
    if (tid < 144) {
        xres = __ldg((const uint2*)(prm.x + qb * DM + r * 72 + qq * 4));
    }
    layernorm_row<false>(xw);
    DBG_T(18);
    {
        uint32_t* act = (uint32_t*)(smem + SM_R2) + warp * (PITCH / 2);
#pragma unroll
        for (int j = 0; j < 9; j++) act[j * 32 + lane] = xw[j];
    }
    asm volatile("bar.sync 0, 320;" ::: "memory");
    asm volatile("barrier.cluster.arrive.relaxed.aligned;" ::: "memory");
    DBG_T(2);

    {
        const int m = warp & 3, kh = warp >> 2;
        float ca[4] = {0.f, 0.f, 0.f, 0.f}, cb[4] = {0.f, 0.f, 0.f, 0.f};
        const int lrow = (lane & 7) + ((lane >> 4) & 1) * 8;
        const int lchunk = m * 2 + ((lane >> 3) & 1);
        const uint32_t baddr = sb + SM_R2 + (lane & 7) * (PITCH * 2) + (lane >> 3) * 16;
#pragma unroll
        for (int j = 0; j < 5; j++) {
            const int nk = j < 4 ? 4 : 2;
            const int ks0 = j * 8 + kh * nk;
            uint32_t bfr[2][4], afr[4][4];
#pragma unroll
            for (int s = 0; s < nk; s += 2) ldsm_x4(bfr[s / 2][0], bfr[s / 2][1], bfr[s / 2][2], bfr[s / 2][3], baddr + (ks0 + s) * 32);
            mbar_wait(BAR(BAR_FULL + j), 0);
#pragma unroll
            for (int s = 0; s < nk; s++) {
                const int row = (ks0 + s) * 16 + lrow;
                ldsm_x4_t(afr[s][0], afr[s][1], afr[s][2], afr[s][3], sb + row * 128 + ((lchunk ^ (row & 7)) << 4));
            }
#pragma unroll
            for (int s = 0; s < nk; s += 2) {
                mma16816(ca, afr[s][0], afr[s][1], afr[s][2], afr[s][3], bfr[s / 2][0], bfr[s / 2][1]);
                mma16816(cb, afr[s + 1][0], afr[s + 1][1], afr[s + 1][2], afr[s + 1][3], bfr[s / 2][2], bfr[s / 2][3]);
            }
            if (j < 4) {
                cons_sync();
                if (warp < 4 && lane == 0) mbar_arrive(BAR(BAR_EMPTY + j));
            }
        }
        DBG_T(19);
        float* red = (float*)(smem + SM_R1);
        red[(kh * 8 + 2 * t) * 64 + m * 16 + g] = ca[0] + cb[0];
        red[(kh * 8 + 2 * t + 1) * 64 + m * 16 + g] = ca[1] + cb[1];
        red[(kh * 8 + 2 * t) * 64 + m * 16 + g + 8] = ca[2] + cb[2];
        red[(kh * 8 + 2 * t + 1) * 64 + m * 16 + g + 8] = ca[3] + cb[3];
        cons_sync();
        if (warp < 4 && lane == 0) mbar_arrive(BAR(BAR_EMPTY + 4));
        asm volatile("barrier.cluster.wait.acquire.aligned;" ::: "memory");
        if (tid < 64) {
            const int b = tid >> 3, oct = tid & 7;
            const float* p0 = red + b * 64 + oct * 8;
            const float4 u0 = *(const float4*)p0, u1 = *(const float4*)(p0 + 4);
            const float4 v0 = *(const float4*)(p0 + 512), v1 = *(const float4*)(p0 + 516);
            const uint4 w = make_uint4(bf16_pack(u0.x + v0.x, u0.y + v0.y), bf16_pack(u0.z + v0.z, u0.w + v0.w),
                                       bf16_pack(u1.x + v1.x, u1.y + v1.y), bf16_pack(u1.z + v1.z, u1.w + v1.w));
            st_async4(mapa(sb + SM_QS + (r * 64 + oct * 8) * 2, b), w, mapa(BAR(BAR_Q), b));
        }
        mbar_wait_cl(BAR(BAR_Q));
        cons_sync();
    }
    DBG_T(3);

    float4 apart = make_float4(0.f, 0.f, 0.f, 0.f);

#pragma unroll 1
    for (int u = 0; u < 2; u++) {
        {
            uint32_t bq[16];
            {
                const int pi = (g >> 1) & 1, h = g & 1;
#pragma unroll
                for (int j = 0; j < 4; j++) {
                    uint4 v = lds128(sb + SM_QS + (u * 2 + h) * 256 + (4 * (j ^ pi) + t) * 16);
                    if (g >= 4) v = make_uint4(0, 0, 0, 0);
                    bq[4 * j] = v.x; bq[4 * j + 1] = v.y; bq[4 * j + 2] = v.z; bq[4 * j + 3] = v.w;
                }
            }
            const int pig = g & 1;
            const int first = (u ? IT_KB : IT_KA) + (warp >> 2);
            int slot = first % NS; uint32_t ph = (first / NS) & 1;
            const uint32_t rowoff = ((warp & 3) * 16 + g) * 256;
            unsigned short* sc = (unsigned short*)(smem + SM_R1);
            float mx0 = -INFINITY, mx1 = -INFINITY;
            for (int kt = warp >> 2; kt < 32; kt += 2) {
                mbar_wait(BAR(BAR_FULL + slot), ph);
                const uint32_t base = sb + slot * SLOT + rowoff;
                uint4 X[4], Y[4];
#pragma unroll
                for (int j = 0; j < 4; j++) {
                    const uint32_t a = base + (4 * (j ^ pig) + t) * 16;
                    X[j] = lds128(a); Y[j] = lds128(a + 2048);
                }
                float ca[4] = {0.f, 0.f, 0.f, 0.f}, cb[4] = {0.f, 0.f, 0.f, 0.f};
#pragma unroll
                for (int j = 0; j < 4; j++) {
                    mma16816(ca, X[j].x, Y[j].x, X[j].y, Y[j].y, bq[4 * j], bq[4 * j + 1]);
                    mma16816(cb, X[j].z, Y[j].z, X[j].w, Y[j].w, bq[4 * j + 2], bq[4 * j + 3]);
                }
                __syncwarp();
                if (lane == 0) mbar_arrive(BAR(BAR_EMPTY + slot));
                if (t == pig) {
                    const int key = kt * 64 + (warp & 3) * 16 + g;
                    const float scale = 0.08838834764831845f;
                    const uint32_t s0 = bf16_pack(bf16r(ca[0] + cb[0]) * scale, bf16r(ca[2] + cb[2]) * scale);
                    const uint32_t s1 = bf16_pack(bf16r(ca[1] + cb[1]) * scale, bf16r(ca[3] + cb[3]) * scale);
                    sc[key] = (unsigned short)s0; sc[key + 8] = (unsigned short)(s0 >> 16);
                    sc[2048 + key] = (unsigned short)s1; sc[2048 + key + 8] = (unsigned short)(s1 >> 16);
                    mx0 = fmaxf(mx0, fmaxf(bf_lo(s0), bf_hi(s0)));
                    mx1 = fmaxf(mx1, fmaxf(bf_lo(s1), bf_hi(s1)));
                }
                slot += 2; if (slot >= NS) { slot -= NS; ph ^= 1; }
            }
            mx0 = warp_max(mx0); mx1 = warp_max(mx1);
            if (lane == 0) { float* stat = (float*)(smem + SM_STAT); stat[warp] = mx0; stat[8 + warp] = mx1; }
        }
        cons_sync();
        if (u == 0) DBG_T(4); else DBG_T(7);

        {
            const int h = tid >> 7, idx = tid & 127;
            const uint32_t a = sb + SM_R1 + h * 4096 + idx * 32;
            const uint4 u0 = lds128(a), u1 = lds128(a + 16);
            float e[16];
            e[0] = bf_lo(u0.x); e[1] = bf_hi(u0.x); e[2] = bf_lo(u0.y); e[3] = bf_hi(u0.y);
            e[4] = bf_lo(u0.z); e[5] = bf_hi(u0.z); e[6] = bf_lo(u0.w); e[7] = bf_hi(u0.w);
            e[8] = bf_lo(u1.x); e[9] = bf_hi(u1.x); e[10] = bf_lo(u1.y); e[11] = bf_hi(u1.y);
            e[12] = bf_lo(u1.z); e[13] = bf_hi(u1.z); e[14] = bf_lo(u1.w); e[15] = bf_hi(u1.w);
            float* stat = (float*)(smem + SM_STAT);
            const float4 ma = *(const float4*)(stat + h * 8), mb = *(const float4*)(stat + h * 8 + 4);
            const float mx = fmaxf(fmaxf(fmaxf(ma.x, ma.y), fmaxf(ma.z, ma.w)), fmaxf(fmaxf(mb.x, mb.y), fmaxf(mb.z, mb.w)));
            float sum = 0.f;
#pragma unroll
            for (int i = 0; i < 16; i++) {
                asm("ex2.approx.ftz.f32 %0, %1;" : "=f"(e[i]) : "f"((e[i] - mx) * 1.4426950408889634f));
                sum += e[i];
            }
            sum = warp_sum(sum);
            if (lane == 0) stat[16 + warp] = sum;
            cons_sync();
            sum = (stat[16 + h * 4] + stat[16 + h * 4 + 1]) + (stat[16 + h * 4 + 2] + stat[16 + h * 4 + 3]);
            const float inv = __fdiv_rn(1.0f, sum);
            uint32_t w[8];
#pragma unroll
            for (int i = 0; i < 8; i++) w[i] = bf16_pack(e[2 * i] * inv, e[2 * i + 1] * inv);
            *(uint4*)(smem + SM_R1 + h * 4096 + idx * 32) = make_uint4(w[0], w[1], w[2], w[3]);
            *(uint4*)(smem + SM_R1 + h * 4096 + idx * 32 + 16) = make_uint4(w[4], w[5], w[6], w[7]);
            cons_sync();
        }
        if (u == 0) DBG_T(5);

        {
            float acc[2][4][4];
#pragma unroll
            for (int a = 0; a < 2; a++)
#pragma unroll
                for (int b = 0; b < 4; b++)
#pragma unroll
                    for (int d = 0; d < 4; d++) acc[a][b][d] = 0.f;
            const int first = (u ? IT_VB : IT_VA) + (warp >> 2);
            const bool bvalid = (g >> 1) == t;
            const uint32_t paddr = sb + SM_R1 + (g & 1) * 4096 + ((warp & 3) * 16 + 4 * t) * 2;
            const uint32_t rowoff = ((warp & 3) * 16 + 4 * t) * 256 + (g ^ (2 * t)) * 16;
            for (int vt = warp >> 2; vt < 32; vt += 2) {
                const int item = first - (warp >> 2) + vt;
                const int slot = item_slot(item);
                const uint2 pbv = lds64(paddr + vt * 128);
                const uint32_t b0 = bvalid ? pbv.x : 0u, b1 = bvalid ? pbv.y : 0u;
                mbar_wait(BAR(BAR_FULL + slot), item_par(item));
                if (u == 1 && vt == TRIG_TILE && tid == 0) mbar_arrive(BAR(BAR_TRIG));
                const uint32_t base = sb + slot * SLOT + rowoff;
                uint4 X[2][4];
#pragma unroll
                for (int hf = 0; hf < 2; hf++)
#pragma unroll
                    for (int i = 0; i < 4; i++) X[hf][i] = lds128(base + i * 256 + hf * 128);
#pragma unroll
                for (int hf = 0; hf < 2; hf++) {
                    const uint32_t x0[4] = {X[hf][0].x, X[hf][0].y, X[hf][0].z, X[hf][0].w};
                    const uint32_t x1[4] = {X[hf][1].x, X[hf][1].y, X[hf][1].z, X[hf][1].w};
                    const uint32_t x2[4] = {X[hf][2].x, X[hf][2].y, X[hf][2].z, X[hf][2].w};
                    const uint32_t x3[4] = {X[hf][3].x, X[hf][3].y, X[hf][3].z, X[hf][3].w};
#pragma unroll
                    for (int m = 0; m < 4; m++) {
                        mma16816(acc[hf][m], __byte_perm(x0[m], x1[m], 0x5410), __byte_perm(x0[m], x1[m], 0x7632),
                                 __byte_perm(x2[m], x3[m], 0x5410), __byte_perm(x2[m], x3[m], 0x7632), b0, b1);
                    }
                }
                __syncwarp();
                if (lane == 0) mbar_arrive(BAR(BAR_EMPTY + slot));
            }
            if (u == 0) DBG_T(6); else DBG_T(8);
            float k1[4][4];
            {
                const bool up = (t & 2) != 0;
#pragma unroll
                for (int m = 0; m < 4; m++)
#pragma unroll
                    for (int d = 0; d < 4; d++) {
                        const float keep = up ? acc[1][m][d] : acc[0][m][d];
                        const float send = up ? acc[0][m][d] : acc[1][m][d];
                        k1[m][d] = keep + __shfl_xor_sync(0xffffffffu, send, 18);
                    }
            }
            float k2[2][4];
            {
                const bool up = (t & 1) != 0;
#pragma unroll
                for (int m = 0; m < 2; m++)
#pragma unroll
                    for (int d = 0; d < 4; d++) {
                        const float keep = up ? k1[2 + m][d] : k1[m][d];
                        const float send = up ? k1[m][d] : k1[2 + m][d];
                        k2[m][d] = keep + __shfl_xor_sync(0xffffffffu, send, 9);
                    }
            }
            float* red = (float*)(smem + SM_R2);
            {
                const int d0 = ((g ^ (2 * t)) + 8 * (t >> 1)) * 8 + (t & 1) * 4;
                *(float4*)(red + warp * 256 + d0) = make_float4(k2[0][0], k2[0][2], k2[1][0], k2[1][2]);
                *(float4*)(red + warp * 256 + 128 + d0) = make_float4(k2[0][1], k2[0][3], k2[1][1], k2[1][3]);
            }
            cons_sync();
            float s = 0.f;
#pragma unroll
            for (int w = 0; w < 8; w++) s += red[w * 256 + tid];
            const uint32_t obuf = sb + SM_R3 + u * (NB * OPITCH * 2);
            const uint32_t obar = BAR(u ? BAR_OB : BAR_OA);
            ((unsigned short*)(smem + SM_OL))[tid] = (unsigned short)bf16_bits(s);
            cons_sync();
            const uint4 ov = lds128(sb + SM_OL + lane * 16);
            st_async4(mapa(obuf + r * (OPITCH * 2) + lane * 16, warp), ov, mapa(obar, warp));
            if (u == 0) {
#pragma unroll
                for (int j = 0; j < 3; j++) mbar_wait(BAR(BAR_FULL + (IT_WOA + j) % NS), ((IT_WOA + j) / NS) & 1);
            } else {
#pragma unroll
                for (int j = 0; j < 3; j++) mbar_wait(BAR(BAR_TW + j), 0);
            }
            const uint32_t wbase = u ? sb + TAIL : sb + (IT_WOA % NS) * SLOT;
            const uint32_t wstride = u ? CHUNK : SLOT;
            uint32_t af[4][3][4];
            gemv_load<4>(af, [&](int k) { return wbase + k * wstride; }, tid);
            mbar_wait_cl(obar);
            if (u == 1) DBG_T(9);
            const float4 p = gemv_mma<4>(af, obuf, OPITCH, (float*)(smem + SM_R2), tid);
            apart.x += p.x; apart.y += p.y; apart.z += p.z; apart.w += p.w;
            if (u == 0) {
                if (warp < 4 && lane == 0) {
#pragma unroll
                    for (int j = 0; j < 3; j++) mbar_arrive(BAR(BAR_EMPTY + (IT_WOA + j) % NS));
                }
                cons_sync();
            }
        }
    }

    uint32_t hw0 = 0, hw1 = 0;
    uint32_t af[9][3][4];
    if (tid < 144) {
        mbar_wait(BAR(BAR_RSTOK), 0);
        st_pub4(&g_scr.ap[r][cl][tid * 4], make_uint4(f2pub(apart.x), f2pub(apart.y), f2pub(apart.z), f2pub(apart.w)));
        DBG_T(10);
    }
    if (tid < 144) {
        { const long long c0 = clock64(); while (clock64() - c0 < POLL_DELAY) { } }
        uint4 v[NCL];
        const uint32_t* ap0 = &g_scr.ap[r][0][tid * 4];
        uint32_t spins = 0;
        while (true) {
#pragma unroll
            for (int c = 0; c < NCL; c++) v[c] = ld_poll4(ap0 + c * 576);
            uint32_t bad = 0;
#pragma unroll
            for (int c = 0; c < NCL; c++)
                bad |= (uint32_t)(v[c].x == SENT) | (uint32_t)(v[c].y == SENT) | (uint32_t)(v[c].z == SENT) | (uint32_t)(v[c].w == SENT);
            if (bad == 0) break;
            if (++spins > (1u << 22)) __trap();
        }
        float s0 = 0.f, s1 = 0.f, s2 = 0.f, s3 = 0.f;
#pragma unroll
        for (int c = 0; c < NCL; c++) {
            s0 += __uint_as_float(v[c].x); s1 += __uint_as_float(v[c].y);
            s2 += __uint_as_float(v[c].z); s3 += __uint_as_float(v[c].w);
        }
        if (tid == 0) mbar_arrive(BAR(BAR_WOFREE));
        DBG_T(25);
        const float h0 = bf16r(bf_lo(xres.x) + bf16r(s0)), h1 = bf16r(bf_hi(xres.x) + bf16r(s1));
        const float h2 = bf16r(bf_lo(xres.y) + bf16r(s2)), h3 = bf16r(bf_hi(xres.y) + bf16r(s3));
        hw0 = bf16_pack(h0, h1); hw1 = bf16_pack(h2, h3);
        if (qb == cl) *(float4*)(smem + SM_HS + qq * 16) = make_float4(h0, h1, h2, h3);
    }
    __syncwarp();
    if (warp < 5) send_slice(hw0, hw1, sb + SM_R1, BAR(BAR_H), r, tid);
    DBG_T(11);
    {
        const int c0 = (9 * (warp & 3)) / 6;
        mbar_wait(BAR(BAR_TW + 3 + c0), 0);
        mbar_wait(BAR(BAR_TW + 3 + c0 + 1), 0);
    }
    DBG_T(27);
    gemv_load<9>(af, [&](int k) { return sb + TAIL_W1 + k * CHUNK; }, tid);
    mbar_wait_cl(BAR(BAR_H));
    DBG_T(20);
    {
        uint32_t* row = (uint32_t*)(smem + SM_R1) + warp * (PITCH / 2);
        uint32_t w[9];
#pragma unroll
        for (int j = 0; j < 9; j++) w[j] = row[j * 32 + lane];
        layernorm_row<true>(w);
#pragma unroll
        for (int j = 0; j < 9; j++) row[j * 32 + lane] = w[j];
    }
    DBG_T(21);
    cons_sync();
    DBG_T(12);

    float4 p = gemv_mma<9>(af, sb + SM_R1, PITCH, (float*)(smem + SM_R2), tid);
    {
        float a = bf16r(p.x), b = bf16r(p.y), c = bf16r(p.z), d = bf16r(p.w);
        a = (a != a) ? a : fmaxf(a, 0.f); b = (b != b) ? b : fmaxf(b, 0.f);
        c = (c != c) ? c : fmaxf(c, 0.f); d = (d != d) ? d : fmaxf(d, 0.f);
        DBG_T(22);
        __syncwarp();
        if (warp < 5) send_slice(bf16_pack(a, b), bf16_pack(c, d), sb + SM_R3, BAR(BAR_H1), r, tid);
        DBG_T(23);
    }
    {
        auto addr = [&](int k) { return k < 4 ? sb + k * SLOT : sb + TAIL + (k - 4) * CHUNK; };
        auto wait = [&](int k) { mbar_wait(BAR(BAR_TW + 9 + k), 0); };
        auto awaitf = [&]() { mbar_wait_cl(BAR(BAR_H1)); DBG_T(13); };
        if (tid < 128) gemv_w2_t<3>(af, addr, wait, awaitf, sb + SM_R3, PITCH, (float*)(smem + SM_R2), tid);
        else gemv_w2_t<2>(af, addr, wait, awaitf, sb + SM_R3, PITCH, (float*)(smem + SM_R2), tid);
    }
    cons_sync();
    if (tid < 144) {
        const float* red = (const float*)(smem + SM_R2);
        const float4 p0 = *(const float4*)(red + tid * 4), p1 = *(const float4*)(red + 576 + tid * 4);
        const float4 p2 = *(const float4*)(red + 1152 + tid * 4), p3 = *(const float4*)(red + 1728 + tid * 4);
        p.x = (p0.x + p1.x) + (p2.x + p3.x); p.y = (p0.y + p1.y) + (p2.y + p3.y);
        p.z = (p0.z + p1.z) + (p2.z + p3.z); p.w = (p0.w + p1.w) + (p2.w + p3.w);
    }
    {
        if (tid < 144) {
            st_pub4(&g_scr.fp[r][cl][tid * 4], make_uint4(f2pub(p.x), f2pub(p.y), f2pub(p.z), f2pub(p.w)));
            DBG_T(14);
            { const long long c0 = clock64(); while (clock64() - c0 < POLL_DELAY) { } }
            const int quad = tid >> 3, c = tid & 7;
            uint4 w;
            uint32_t spins = 0;
            while (true) {
                w = ld_poll4(&g_scr.fp[r][c][cl * 72 + quad * 4]);
                if (vec_valid(w)) break;
                if (++spins > (1u << 22)) __trap();
            }
            apart = make_float4(__uint_as_float(w.x), __uint_as_float(w.y), __uint_as_float(w.z), __uint_as_float(w.w));
        } else {
            apart = make_float4(0.f, 0.f, 0.f, 0.f);
        }
        if (warp < 5) {
            __syncwarp();
#pragma unroll
            for (int o = 1; o < 8; o <<= 1) {
                apart.x += __shfl_xor_sync(0xffffffffu, apart.x, o); apart.y += __shfl_xor_sync(0xffffffffu, apart.y, o);
                apart.z += __shfl_xor_sync(0xffffffffu, apart.z, o); apart.w += __shfl_xor_sync(0xffffffffu, apart.w, o);
            }
            if (tid < 144 && (tid & 7) == 0) {
                const int quad = tid >> 3;
                const float4 h = *(const float4*)(smem + SM_HS + quad * 16);
                uint2 o;
                o.x = bf16_pack(h.x + bf16r(apart.x), h.y + bf16r(apart.y));
                o.y = bf16_pack(h.z + bf16r(apart.z), h.w + bf16r(apart.w));
                *(uint2*)(prm.out + cl * DM + r * 72 + quad * 4) = o;
            }
            if (blockIdx.x == 0 && tid == 0) g_cnt = 0;
            DBG_T(15);
        }
    }
}

typedef CUresult (*EncodeTiledFn)(CUtensorMap*, CUtensorMapDataType, cuuint32_t, void*, const cuuint64_t*, const cuuint64_t*,
                                  const cuuint32_t*, const cuuint32_t*, CUtensorMapInterleave, CUtensorMapSwizzle,
                                  CUtensorMapL2promotion, CUtensorMapFloatOOBfill);

void make_map(EncodeTiledFn fn, CUtensorMap* m, const void* ptr, uint64_t cols, uint64_t rows, uint32_t bc, uint32_t br,
              CUtensorMapSwizzle sw) {
    cuuint64_t dims[2] = {cols, rows};
    cuuint64_t strides[1] = {cols * 2};
    cuuint32_t box[2] = {bc, br};
    cuuint32_t es[2] = {1, 1};
    fn(m, CU_TENSOR_MAP_DATA_TYPE_BFLOAT16, 2, const_cast<void*>(ptr), dims, strides, box, es, CU_TENSOR_MAP_INTERLEAVE_NONE, sw,
       CU_TENSOR_MAP_L2_PROMOTION_L2_256B, CU_TENSOR_MAP_FLOAT_OOB_FILL_NONE);
}

}

extern "C" void kernel_launch(void* const* d_in, const int* in_sizes, int n_in, void* d_out, int out_size) {
    (void)in_sizes; (void)n_in; (void)out_size;
    static EncodeTiledFn enc = nullptr;
    if (!enc) {
        void* fn = nullptr;
        cudaDriverEntryPointQueryResult qr;
        cudaGetDriverEntryPoint("cuTensorMapEncodeTiled", &fn, cudaEnableDefault, &qr);
        enc = (EncodeTiledFn)fn;
        cudaFuncSetAttribute(fused_decode_kernel, cudaFuncAttributeMaxDynamicSharedMemorySize, SM_TOTAL);
    }
    CUtensorMap mq, mo, m1, m2;
    make_map(enc, &mq, d_in[3], 4096, DM, 64, 128, CU_TENSOR_MAP_SWIZZLE_128B);
    make_map(enc, &mo, d_in[4], DM, 4096, 72, 32, CU_TENSOR_MAP_SWIZZLE_NONE);
    make_map(enc, &m1, d_in[6], DFF, DM, 72, 96, CU_TENSOR_MAP_SWIZZLE_NONE);
    make_map(enc, &m2, d_in[7], DM, DFF, 72, 96, CU_TENSOR_MAP_SWIZZLE_NONE);
    Params p;
    p.x = (const __nv_bfloat16*)d_in[0];
    p.k = (const __nv_bfloat16*)d_in[1];
    p.v = (const __nv_bfloat16*)d_in[2];
    p.out = (__nv_bfloat16*)d_out;
    fused_decode_kernel<<<NCTA, 320, SM_TOTAL, cudaStreamPerThread>>>(mq, mo, m1, m2, p);
}
```

```cpp
#include <cuda_runtime.h>
#include <cuda_bf16.h>
#include <cuda.h>
#include <stdint.h>

namespace {

constexpr int NB = 8;
constexpr int DM = 576;
constexpr int HKV = 16;
constexpr int DH = 128;
constexpr int SK = 8192;
constexpr int WIN = 2048;
constexpr int DFF = 4608;
constexpr int NCL = 8;
constexpr int CS = 8;
constexpr int NCTA = NCL * CS;

constexpr int SLOT = 16384;
constexpr int NS = 12;
constexpr int IT_KA = 5, IT_VA = 37, IT_WOA = 69, IT_KB = 72, IT_VB = 104, IT_FIFO_END = 128;
constexpr int CHUNK = 96 * 144;
constexpr int TAIL = 4 * SLOT;
constexpr int TAIL_W1 = TAIL + 256 * 144;

#define POLL_DELAY 300
#define TRIG_TILE 8
#define BURST 6
#define SPIN_CL 1
#define INFLIGHT 10

constexpr int PITCH = 584;
constexpr int OPITCH = 264;
constexpr int SM_R1 = NS * SLOT;
constexpr int SM_R2 = SM_R1 + NB * PITCH * 2;
constexpr int SM_R3 = SM_R2 + NB * PITCH * 2;
constexpr int SM_QS = SM_R3 + NB * PITCH * 2;
constexpr int SM_HS = SM_QS + 1024;
constexpr int SM_OL = SM_HS + 288;
constexpr int SM_STAT = SM_OL + 512;
constexpr int SM_BAR = SM_STAT + 96;
constexpr int BAR_FULL = 0, BAR_EMPTY = 12, BAR_TW = 24, BAR_Q = 39, BAR_OA = 40, BAR_OB = 41, BAR_H = 42, BAR_H1 = 43,
              BAR_WOFREE = 44, BAR_TRIG = 45, BAR_RSTOK = 46, NBAR = 47;
constexpr int SM_DBG = SM_BAR + NBAR * 8;
constexpr int SM_TOTAL = SM_DBG + 32 * 8;
static_assert(SM_TOTAL <= 232448, "smem");
static_assert(2 * NB * OPITCH * 2 <= NB * PITCH * 2, "o_all");

constexpr uint32_t SENT = 0xffffffffu;

struct Scratch {
    uint32_t ap[CS][NCL][576];
    uint32_t fp[CS][NCL][576];
};
__device__ __align__(128) Scratch g_scr;
__device__ uint32_t g_cnt;

#define DBG_T(i) do { } while (0)

__device__ __forceinline__ uint32_t smem_u32(const void* p) { return (uint32_t)__cvta_generic_to_shared(p); }
__device__ __forceinline__ void mbar_init(uint32_t bar, uint32_t cnt) {
    asm volatile("mbarrier.init.shared::cta.b64 [%0], %1;" ::"r"(bar), "r"(cnt) : "memory");
}
__device__ __forceinline__ void mbar_expect_tx(uint32_t bar, uint32_t bytes) {
    asm volatile("mbarrier.arrive.expect_tx.shared::cta.b64 _, [%0], %1;" ::"r"(bar), "r"(bytes) : "memory");
}
__device__ __forceinline__ void mbar_arrive(uint32_t bar) {
    asm volatile("mbarrier.arrive.shared::cta.b64 _, [%0];" ::"r"(bar) : "memory");
}
__device__ __forceinline__ bool mbar_try(uint32_t bar, uint32_t parity) {
    uint32_t ok;
    asm volatile("{\n.reg .pred p;\nmbarrier.try_wait.parity.shared::cta.b64 p, [%1], %2;\nselp.u32 %0, 1, 0, p;\n}"
                 : "=r"(ok) : "r"(bar), "r"(parity) : "memory");
    return ok != 0;
}
__device__ __forceinline__ void mbar_wait(uint32_t bar, uint32_t parity) {
    uint32_t spins = 0;
    while (!mbar_try(bar, parity)) {
        if (++spins > (1u << 22)) __trap();
    }
}
__device__ __forceinline__ bool mbar_try_cl(uint32_t bar, uint32_t parity) {
    uint32_t ok;
    asm volatile("{\n.reg .pred p;\nmbarrier.test_wait.parity.acquire.cluster.shared::cta.b64 p, [%1], %2;\nselp.u32 %0, 1, 0, p;\n}"
                 : "=r"(ok) : "r"(bar), "r"(parity) : "memory");
    return ok != 0;
}
__device__ __forceinline__ void mbar_wait_cl(uint32_t bar) {
    uint32_t spins = 0;
    while (!mbar_try_cl(bar, 0)) {
        if (++spins > (1u << 26)) __trap();
    }
}
__device__ __forceinline__ void bulk_g2s(uint32_t dst, const void* src, uint32_t bytes, uint32_t bar, uint64_t pol) {
    asm volatile("cp.async.bulk.shared::cluster.global.mbarrier::complete_tx::bytes.L2::cache_hint [%0], [%1], %2, [%3], %4;"
                 ::"r"(dst), "l"(src), "r"(bytes), "r"(bar), "l"(pol) : "memory");
}
__device__ __forceinline__ void tma_2d(uint32_t dst, const CUtensorMap* map, int x, int y, uint32_t bar, uint64_t pol) {
    asm volatile("cp.async.bulk.tensor.2d.shared::cluster.global.mbarrier::complete_tx::bytes.L2::cache_hint [%0], [%1, {%3, %4}], [%2], %5;"
                 ::"r"(dst), "l"(map), "r"(bar), "r"(x), "r"(y), "l"(pol) : "memory");
}
__device__ __forceinline__ void cons_sync() { asm volatile("bar.sync 1, 256;" ::: "memory"); }
__device__ __forceinline__ uint32_t mapa(uint32_t a, uint32_t rank) {
    uint32_t r; asm("mapa.shared::cluster.u32 %0, %1, %2;" : "=r"(r) : "r"(a), "r"(rank)); return r;
}
__device__ __forceinline__ void st_async4(uint32_t addr, uint4 v, uint32_t bar) {
    asm volatile("st.async.weak.shared::cluster.mbarrier::complete_tx::bytes.v4.b32 [%0], {%1,%2,%3,%4}, [%5];"
                 ::"r"(addr), "r"(v.x), "r"(v.y), "r"(v.z), "r"(v.w), "r"(bar) : "memory");
}
__device__ __forceinline__ uint4 lds128(uint32_t a) {
    uint4 v; asm volatile("ld.shared.v4.u32 {%0,%1,%2,%3}, [%4];" : "=r"(v.x), "=r"(v.y), "=r"(v.z), "=r"(v.w) : "r"(a)); return v;
}
__device__ __forceinline__ uint2 lds64(uint32_t a) {
    uint2 v; asm volatile("ld.shared.v2.u32 {%0,%1}, [%2];" : "=r"(v.x), "=r"(v.y) : "r"(a)); return v;
}
__device__ __forceinline__ void ldsm_x4(uint32_t& r0, uint32_t& r1, uint32_t& r2, uint32_t& r3, uint32_t a) {
    asm volatile("ldmatrix.sync.aligned.m8n8.x4.shared.b16 {%0,%1,%2,%3}, [%4];"
                 : "=r"(r0), "=r"(r1), "=r"(r2), "=r"(r3) : "r"(a));
}
__device__ __forceinline__ void ldsm_x2(uint32_t& r0, uint32_t& r1, uint32_t a) {
    asm volatile("ldmatrix.sync.aligned.m8n8.x2.shared.b16 {%0,%1}, [%2];" : "=r"(r0), "=r"(r1) : "r"(a));
}
__device__ __forceinline__ void ldsm_x4_t(uint32_t& r0, uint32_t& r1, uint32_t& r2, uint32_t& r3, uint32_t a) {
    asm volatile("ldmatrix.sync.aligned.m8n8.x4.trans.shared.b16 {%0,%1,%2,%3}, [%4];"
                 : "=r"(r0), "=r"(r1), "=r"(r2), "=r"(r3) : "r"(a));
}
__device__ __forceinline__ void mma16816(float (&c)[4], uint32_t a0, uint32_t a1, uint32_t a2, uint32_t a3, uint32_t b0, uint32_t b1) {
    asm volatile("mma.sync.aligned.m16n8k16.row.col.f32.bf16.bf16.f32 {%0,%1,%2,%3}, {%4,%5,%6,%7}, {%8,%9}, {%0,%1,%2,%3};"
                 : "+f"(c[0]), "+f"(c[1]), "+f"(c[2]), "+f"(c[3])
                 : "r"(a0), "r"(a1), "r"(a2), "r"(a3), "r"(b0), "r"(b1));
}
__device__ __forceinline__ uint4 ld_poll4(const uint32_t* p) {
    uint4 v;
    asm volatile("ld.relaxed.gpu.global.v4.u32 {%0,%1,%2,%3}, [%4];" : "=r"(v.x), "=r"(v.y), "=r"(v.z), "=r"(v.w) : "l"(p) : "memory");
    return v;
}
__device__ __forceinline__ void st_pub4(uint32_t* p, uint4 v) {
    asm volatile("st.relaxed.gpu.global.v4.u32 [%0], {%1,%2,%3,%4};" ::"l"(p), "r"(v.x), "r"(v.y), "r"(v.z), "r"(v.w) : "memory");
}
__device__ __forceinline__ bool vec_valid(const uint4& v) { return v.x != SENT && v.y != SENT && v.z != SENT && v.w != SENT; }
__device__ __forceinline__ uint32_t f2pub(float f) { uint32_t u = __float_as_uint(f); return u == SENT ? 0x7fffffffu : u; }

__device__ __forceinline__ uint32_t bf16_pack(float lo, float hi) {
    uint32_t r; asm("cvt.rn.bf16x2.f32 %0, %1, %2;" : "=r"(r) : "f"(hi), "f"(lo)); return r;
}
__device__ __forceinline__ uint32_t bf16_bits(float f) { return bf16_pack(f, 0.f); }
__device__ __forceinline__ float bf16r(float f) { return __uint_as_float(bf16_pack(0.f, f)); }
__device__ __forceinline__ float bf_lo(uint32_t w) { return __uint_as_float(w << 16); }
__device__ __forceinline__ float bf_hi(uint32_t w) { return __uint_as_float(w & 0xffff0000u); }
__device__ __forceinline__ float warp_sum(float v) {
#pragma unroll
    for (int o = 16; o > 0; o >>= 1) v += __shfl_xor_sync(0xffffffffu, v, o);
    return v;
}
__device__ __forceinline__ float warp_max(float v) {
#pragma unroll
    for (int o = 16; o > 0; o >>= 1) v = fmaxf(v, __shfl_xor_sync(0xffffffffu, v, o));
    return v;
}

template <bool FAST>
__device__ __forceinline__ void layernorm_row(uint32_t (&w)[9]) {
    const float x0 = __shfl_sync(0xffffffffu, bf_lo(w[0]), 0);
    float s0 = 0.f, s1 = 0.f, s2 = 0.f, q0 = 0.f, q1 = 0.f, q2 = 0.f;
#pragma unroll
    for (int j = 0; j < 3; j++) {
        const float a0 = bf_lo(w[j]) - x0, a1 = bf_hi(w[j]) - x0;
        const float b0 = bf_lo(w[3 + j]) - x0, b1 = bf_hi(w[3 + j]) - x0;
        const float c0 = bf_lo(w[6 + j]) - x0, c1 = bf_hi(w[6 + j]) - x0;
        s0 += a0 + a1; s1 += b0 + b1; s2 += c0 + c1;
        q0 = fmaf(a0, a0, fmaf(a1, a1, q0)); q1 = fmaf(b0, b0, fmaf(b1, b1, q1)); q2 = fmaf(c0, c0, fmaf(c1, c1, q2));
    }
    float s = (s0 + s1) + s2, q = (q0 + q1) + q2;
#pragma unroll
    for (int o = 16; o > 0; o >>= 1) { s += __shfl_xor_sync(0xffffffffu, s, o); q += __shfl_xor_sync(0xffffffffu, q, o); }
    const float md = s * (1.0f / 576.0f);
    const float m_b = bf16r(x0 + md);
    const float var_b = bf16r(fmaxf(q * (1.0f / 576.0f) - md * md, 0.f));
    float sq, inv;
    if (FAST) asm("sqrt.approx.f32 %0, %1;" : "=f"(sq) : "f"(bf16r(var_b + 1e-5f)));
    else sq = __fsqrt_rn(bf16r(var_b + 1e-5f));
    const float sd = bf16r(sq);
    if (FAST) asm("rcp.approx.f32 %0, %1;" : "=f"(inv) : "f"(sd));
    else inv = __frcp_rn(sd);
#pragma unroll
    for (int j = 0; j < 9; j++) {
        const uint32_t c = bf16_pack(bf_lo(w[j]) - m_b, bf_hi(w[j]) - m_b);
        w[j] = bf16_pack(bf_lo(c) * inv, bf_hi(c) * inv);
    }
}

__device__ __forceinline__ int item_slot(int i) { return i < IT_FIFO_END ? i % NS : (i - IT_FIFO_END) & 3; }
__device__ __forceinline__ uint32_t item_par(int i) { return i < IT_FIFO_END ? (i / NS) & 1 : (i < IT_FIFO_END + 4 ? 1u : 0u); }

template <int KQ, int NT, typename ChunkAddr>
__device__ __forceinline__ void gemv_load_t(uint32_t (&af)[KQ][3][4], ChunkAddr chunk_addr, int tid) {
    const int warp = tid >> 5, lane = tid & 31;
    const int kq = warp & 3, mg = warp >> 2;
    const int lrow = (lane & 7) + ((lane >> 4) & 1) * 8;
    const int lcol = ((lane >> 3) & 1) * 16;
#pragma unroll
    for (int s = 0; s < KQ; s++) {
        const int ks = kq * KQ + s;
        const uint32_t a = chunk_addr(ks / 6) + ((ks % 6) * 16 + lrow) * 144 + lcol + mg * 96;
#pragma unroll
        for (int m = 0; m < NT; m++) ldsm_x4_t(af[s][m][0], af[s][m][1], af[s][m][2], af[s][m][3], a + m * 32);
    }
}
template <int KQ, typename ChunkAddr>
__device__ __forceinline__ void gemv_load(uint32_t (&af)[KQ][3][4], ChunkAddr chunk_addr, int tid) {
    if (tid < 128) gemv_load_t<KQ, 3>(af, chunk_addr, tid);
    else gemv_load_t<KQ, 2>(af, chunk_addr, tid);
}
template <int KQ, int NT>
__device__ __forceinline__ void gemv_mma_t(const uint32_t (&af)[KQ][3][4], uint32_t act, int apitch, float* red, int tid) {
    const int warp = tid >> 5, lane = tid & 31, g = lane >> 2, t = lane & 3;
    const int kq = warp & 3, mg = warp >> 2;
    float acc[NT][4], acd[NT][4];
#pragma unroll
    for (int m = 0; m < NT; m++) {
        acc[m][0] = acc[m][1] = acc[m][2] = acc[m][3] = 0.f;
        acd[m][0] = acd[m][1] = acd[m][2] = acd[m][3] = 0.f;
    }
    const uint32_t baddr = act + (lane & 7) * (apitch * 2) + (lane >> 3) * 16 + kq * KQ * 32;
    uint32_t bf[KQ + 1][2];
#pragma unroll
    for (int s = 0; s + 1 < KQ; s += 2) ldsm_x4(bf[s][0], bf[s][1], bf[s + 1][0], bf[s + 1][1], baddr + s * 32);
    if (KQ & 1) ldsm_x2(bf[KQ - 1][0], bf[KQ - 1][1], act + (lane & 7) * (apitch * 2) + ((lane >> 3) & 1) * 16 + (kq * KQ + KQ - 1) * 32);
#pragma unroll
    for (int s = 0; s < KQ; s++) {
#pragma unroll
        for (int m = 0; m < NT; m++) {
            if (s & 1) mma16816(acd[m], af[s][m][0], af[s][m][1], af[s][m][2], af[s][m][3], bf[s][0], bf[s][1]);
            else mma16816(acc[m], af[s][m][0], af[s][m][1], af[s][m][2], af[s][m][3], bf[s][0], bf[s][1]);
        }
    }
    float* rp = red + kq * 576;
#pragma unroll
    for (int m = 0; m < NT; m++) {
        const int col = mg * 48 + m * 16 + g;
        rp[(2 * t) * 72 + col] = acc[m][0] + acd[m][0];
        rp[(2 * t + 1) * 72 + col] = acc[m][1] + acd[m][1];
        if (NT == 3 || m == 0) {
            rp[(2 * t) * 72 + col + 8] = acc[m][2] + acd[m][2];
            rp[(2 * t + 1) * 72 + col + 8] = acc[m][3] + acd[m][3];
        }
    }
}
__device__ __forceinline__ int il_step(int kq, int s) {
    const int base = 12 * (s / 3), i = s % 3;
    if (kq < 2) return base + (i < 2 ? 2 * kq + i : 6 + kq);
    return base + (i == 0 ? 2 + kq : 4 + 2 * kq + i - 1);
}
template <int NT, typename ChunkAddr, typename ChunkWait, typename ActWait>
__device__ __forceinline__ void gemv_w2_t(uint32_t (&af)[9][3][4], ChunkAddr chunk_addr, ChunkWait chunk_wait, ActWait act_wait,
                                          uint32_t act, int apitch, float* red, int tid) {
    const int warp = tid >> 5, lane = tid & 31, g = lane >> 2, t = lane & 3;
    const int kq = warp & 3, mg = warp >> 2;
    const int lrow = (lane & 7) + ((lane >> 4) & 1) * 8;
    const int lcol = ((lane >> 3) & 1) * 16;
    auto load = [&](int s) {
        const int ks = il_step(kq, s);
        if (s % 3 != 1) chunk_wait(2 * (s / 3) + ((s % 3) == 2));
        else if (kq >= 2) chunk_wait(2 * (s / 3) + 1);
        const uint32_t a = chunk_addr(ks / 6) + ((ks % 6) * 16 + lrow) * 144 + lcol + mg * 96;
#pragma unroll
        for (int m = 0; m < NT; m++) ldsm_x4_t(af[s][m][0], af[s][m][1], af[s][m][2], af[s][m][3], a + m * 32);
    };
#pragma unroll
    for (int s = 0; s < 6; s++) load(s);
    act_wait();
    float acc[NT][4], acd[NT][4];
#pragma unroll
    for (int m = 0; m < NT; m++) {
        acc[m][0] = acc[m][1] = acc[m][2] = acc[m][3] = 0.f;
        acd[m][0] = acd[m][1] = acd[m][2] = acd[m][3] = 0.f;
    }
    const uint32_t baddr = act + (lane & 7) * (apitch * 2) + ((lane >> 3) & 1) * 16;
    uint32_t bf[9][2];
#pragma unroll
    for (int s = 0; s < 9; s++) ldsm_x2(bf[s][0], bf[s][1], baddr + il_step(kq, s) * 32);
#pragma unroll
    for (int s = 0; s < 6; s++) {
#pragma unroll
        for (int m = 0; m < NT; m++) {
            if (s & 1) mma16816(acd[m], af[s][m][0], af[s][m][1], af[s][m][2], af[s][m][3], bf[s][0], bf[s][1]);
            else mma16816(acc[m], af[s][m][0], af[s][m][1], af[s][m][2], af[s][m][3], bf[s][0], bf[s][1]);
        }
    }
#pragma unroll
    for (int s = 6; s < 9; s++) load(s);
#pragma unroll
    for (int s = 6; s < 9; s++) {
#pragma unroll
        for (int m = 0; m < NT; m++) {
            if (s & 1) mma16816(acd[m], af[s][m][0], af[s][m][1], af[s][m][2], af[s][m][3], bf[s][0], bf[s][1]);
            else mma16816(acc[m], af[s][m][0], af[s][m][1], af[s][m][2], af[s][m][3], bf[s][0], bf[s][1]);
        }
    }
    float* rp = red + kq * 576;
#pragma unroll
    for (int m = 0; m < NT; m++) {
        const int col = mg * 48 + m * 16 + g;
        rp[(2 * t) * 72 + col] = acc[m][0] + acd[m][0];
        rp[(2 * t + 1) * 72 + col] = acc[m][1] + acd[m][1];
        if (NT == 3 || m == 0) {
            rp[(2 * t) * 72 + col + 8] = acc[m][2] + acd[m][2];
            rp[(2 * t + 1) * 72 + col + 8] = acc[m][3] + acd[m][3];
        }
    }
}
template <int KQ>
__device__ __forceinline__ float4 gemv_mma(const uint32_t (&af)[KQ][3][4], uint32_t act, int apitch, float* red, int tid) {
    if (tid < 128) gemv_mma_t<KQ, 3>(af, act, apitch, red, tid);
    else gemv_mma_t<KQ, 2>(af, act, apitch, red, tid);
    cons_sync();
    float4 o = make_float4(0.f, 0.f, 0.f, 0.f);
    if (tid < 144) {
        const float4 p0 = *(const float4*)(red + tid * 4), p1 = *(const float4*)(red + 576 + tid * 4);
        const float4 p2 = *(const float4*)(red + 1152 + tid * 4), p3 = *(const float4*)(red + 1728 + tid * 4);
        o.x = (p0.x + p1.x) + (p2.x + p3.x); o.y = (p0.y + p1.y) + (p2.y + p3.y);
        o.z = (p0.z + p1.z) + (p2.z + p3.z); o.w = (p0.w + p1.w) + (p2.w + p3.w);
    }
    return o;
}

__device__ __forceinline__ void send_slice(uint32_t w0, uint32_t w1, uint32_t buf, uint32_t bar, int rank, int tid) {
    const uint32_t n0 = __shfl_xor_sync(0xffffffffu, w0, 1), n1 = __shfl_xor_sync(0xffffffffu, w1, 1);
    if (tid < 144) {
        const int b = tid / 18, quad = tid - b * 18, odd = quad & 1;
        const uint4 v = odd ? make_uint4(n0, n1, w0, w1) : make_uint4(w0, w1, n0, n1);
        const uint32_t a = buf + (b * PITCH + rank * 72 + (quad & ~1) * 4) * 2;
#pragma unroll
        for (int d = 0; d < 4; d++) {
            const int dest = odd * 4 + d;
            st_async4(mapa(a, dest), v, mapa(bar, dest));
        }
    }
}

struct Params {
    const __nv_bfloat16* x;
    const __nv_bfloat16* k;
    const __nv_bfloat16* v;
    __nv_bfloat16* out;
};

__global__ void __cluster_dims__(CS, 1, 1) __launch_bounds__(320, 1)
fused_decode_kernel(const __grid_constant__ CUtensorMap map_wq, const __grid_constant__ CUtensorMap map_wo,
                    const __grid_constant__ CUtensorMap map_w1, const __grid_constant__ CUtensorMap map_w2,
                    const Params prm)
{
    extern __shared__ __align__(1024) unsigned char smem[];
    const uint32_t sb = smem_u32(smem);
    const int tid = threadIdx.x, warp = tid >> 5, lane = tid & 31;
    const int cl = blockIdx.x >> 3;
    const int r = blockIdx.x & 7;
    const uint32_t bars = sb + SM_BAR;
    auto BAR = [&](int i) -> uint32_t { return bars + i * 8; };

    constexpr uint64_t pol = 0x12F0000000000000ull;
    int tid_op;
    asm volatile("mov.u32 %0, %1;" : "=r"(tid_op) : "r"(tid));
    if (tid_op == 256) {
        DBG_T(0);
        const char* k0 = (const char*)prm.k + ((size_t)(r * HKV + 2 * cl) * SK + (SK - WIN)) * (DH * 2);
#pragma unroll
        for (int k = 0; k < BURST; k++) {
            mbar_init(BAR(BAR_FULL + k), 1);
            asm volatile("fence.mbarrier_init.release.cluster;" ::: "memory");
            mbar_expect_tx(BAR(BAR_FULL + k), SLOT);
            if (k < IT_KA) tma_2d(sb + k * SLOT, &map_wq, cl * 512 + r * 64, k * 128, BAR(BAR_FULL + k), pol);
            else bulk_g2s(sb + k * SLOT, k0 + (size_t)(k - IT_KA) * SLOT, SLOT, BAR(BAR_FULL + k), pol);
        }
        DBG_T(16);
    } else if (tid_op == 288) {
#pragma unroll 1
        for (int k = BAR_FULL + BURST; k < NBAR; k++) mbar_init(BAR(k), (k >= BAR_EMPTY && k < BAR_TW) ? 4 : 1);
        mbar_expect_tx(BAR(BAR_Q), CS * 128);
        mbar_expect_tx(BAR(BAR_OA), CS * 512);
        mbar_expect_tx(BAR(BAR_OB), CS * 512);
        mbar_expect_tx(BAR(BAR_H), CS * 1152);
        mbar_expect_tx(BAR(BAR_H1), CS * 1152);
        asm volatile("fence.mbarrier_init.release.cluster;" ::: "memory");
    }
    __syncwarp();
    if ((tid_op >> 5) == 9) asm volatile("bar.arrive 0, 320;" ::: "memory");
    if (warp == 8) {
        const char* kv[2][2];
#pragma unroll
        for (int u = 0; u < 2; u++) {
            const size_t off = ((size_t)(r * HKV + 2 * cl + u) * SK + (SK - WIN)) * (DH * 2);
            kv[u][0] = (const char*)prm.k + off;
            kv[u][1] = (const char*)prm.v + off;
        }
        auto issue_fifo = [&](int i) {
            const int slot = item_slot(i);
            const uint32_t dst = sb + slot * SLOT, fb = BAR(BAR_FULL + slot);
            if (i < IT_KA) {
                mbar_expect_tx(fb, SLOT);
                tma_2d(dst, &map_wq, cl * 512 + r * 64, i * 128, fb, pol);
            } else if (i >= IT_WOA && i < IT_KB) {
                const int j = i - IT_WOA, nb = j < 2 ? 3 : 2;
                mbar_expect_tx(fb, nb * 32 * 144);
                for (int u = 0; u < nb; u++) tma_2d(dst + u * 32 * 144, &map_wo, r * 72, cl * 512 + j * 96 + u * 32, fb, pol);
            } else {
                const char* src = i < IT_VA ? kv[0][0] + (size_t)(i - IT_KA) * SLOT
                                : i < IT_WOA ? kv[0][1] + (size_t)(i - IT_VA) * SLOT
                                : i < IT_VB ? kv[1][0] + (size_t)(i - IT_KB) * SLOT
                                            : kv[1][1] + (size_t)(i - IT_VB) * SLOT;
                mbar_expect_tx(fb, SLOT);
                bulk_g2s(dst, src, SLOT, fb, pol);
            }
        };
        int i = BURST;
        asm volatile("bar.sync 0, 320;" ::: "memory");
        asm volatile("barrier.cluster.arrive.relaxed.aligned;" ::: "memory");
        if (lane == 0) {
            for (; i < IT_FIFO_END; i++) {
                if (i >= NS) mbar_wait(BAR(BAR_EMPTY + i % NS), ((i / NS) - 1) & 1);
                if (i >= INFLIGHT) mbar_wait(BAR(BAR_FULL + (i - INFLIGHT) % NS), ((i - INFLIGHT) / NS) & 1);
                issue_fifo(i);
            }
            auto issue_w1 = [&](int k) {
                mbar_expect_tx(BAR(BAR_TW + 3 + k), CHUNK);
                tma_2d(sb + TAIL_W1 + k * CHUNK, &map_w1, cl * 576 + r * 72, k * 96, BAR(BAR_TW + 3 + k), pol);
            };
            auto issue_wob = [&](int j) {
                const int nb = j < 2 ? 3 : 2;
                mbar_expect_tx(BAR(BAR_TW + j), nb * 32 * 144);
                for (int u = 0; u < nb; u++)
                    tma_2d(sb + TAIL + j * CHUNK + u * 32 * 144, &map_wo, r * 72, cl * 512 + 256 + j * 96 + u * 32, BAR(BAR_TW + j), pol);
            };
            auto issue_w2 = [&](int k, uint32_t dst) {
                mbar_expect_tx(BAR(BAR_TW + 9 + k), CHUNK);
                tma_2d(dst, &map_w2, r * 72, cl * 576 + k * 96, BAR(BAR_TW + 9 + k), pol);
            };
            mbar_wait(BAR(BAR_EMPTY + 8), 1); mbar_wait(BAR(BAR_EMPTY + 9), 1);
            mbar_wait(BAR(BAR_EMPTY + 10), 1); mbar_wait(BAR(BAR_EMPTY + 11), 1);
            for (int k = 0; k < 4; k++) { mbar_wait(BAR(BAR_EMPTY + k), 0); issue_fifo(IT_FIFO_END + k); }
            mbar_wait(BAR(BAR_EMPTY + 4), 0); issue_wob(0);
            mbar_wait(BAR(BAR_EMPTY + 5), 0); issue_wob(1);
            mbar_wait(BAR(BAR_EMPTY + 6), 0); issue_wob(2);
            mbar_wait(BAR(BAR_EMPTY + 7), 0);
            for (int k = 0; k < 4; k++) { mbar_wait(BAR(BAR_EMPTY + k), 1); issue_fifo(IT_FIFO_END + 4 + k); }
            mbar_wait(BAR(BAR_FULL + 3), 0);
            for (int k = 0; k < 6; k++) issue_w1(k);
            mbar_wait(BAR(BAR_TW + 3 + 5), 0);
            for (int k = 0; k < 4; k++) { mbar_wait(BAR(BAR_EMPTY + k), 0); issue_w2(k, sb + k * SLOT); }
            mbar_wait(BAR(BAR_WOFREE), 0);
            issue_w2(4, sb + TAIL); issue_w2(5, sb + TAIL + CHUNK);
            DBG_T(1);
        }
        return;
    }

    if (warp == 9) {
        asm volatile("barrier.cluster.arrive.relaxed.aligned;" ::: "memory");
        if (lane >= 1 && lane < 4) {
            const CUtensorMap* mp = lane == 1 ? &map_wo : lane == 2 ? &map_w1 : &map_w2;
            asm volatile("prefetch.tensormap [%0];" ::"l"(mp) : "memory");
        }
        mbar_wait(BAR(BAR_TRIG), 0);
        for (int i = lane; i < 144; i += 32) {
            st_pub4(&g_scr.ap[r][cl][i * 4], make_uint4(SENT, SENT, SENT, SENT));
            st_pub4(&g_scr.fp[r][cl][i * 4], make_uint4(SENT, SENT, SENT, SENT));
        }
        __threadfence();
        __syncwarp();
        if (lane == 0) {
            __threadfence();
            asm volatile("red.relaxed.gpu.global.add.u32 [%0], 1;" ::"l"(&g_cnt) : "memory");
            uint32_t c, spins = 0;
            do {
                asm volatile("ld.acquire.gpu.global.u32 %0, [%1];" : "=r"(c) : "l"(&g_cnt) : "memory");
                if (++spins > (1u << 22)) __trap();
            } while (c < NCTA);
            mbar_arrive(BAR(BAR_RSTOK));
        }
        return;
    }

    const int g = lane >> 2, t = lane & 3;
    uint32_t xw[9];
    {
        const uint32_t* xr = (const uint32_t*)(prm.x + warp * DM);
#pragma unroll
        for (int j = 0; j < 9; j++) xw[j] = __ldg(xr + j * 32 + lane);
    }
    const int qb = tid / 18, qq = tid - qb * 18;
    uint2 xres = make_uint2(0, 0);
    if (tid < 144) {
        xres = __ldg((const uint2*)(prm.x + qb * DM + r * 72 + qq * 4));
    }
    layernorm_row<false>(xw);
    DBG_T(18);
    {
        uint32_t* act = (uint32_t*)(smem + SM_R2) + warp * (PITCH / 2);
#pragma unroll
        for (int j = 0; j < 9; j++) act[j * 32 + lane] = xw[j];
    }
    asm volatile("bar.sync 0, 320;" ::: "memory");
    asm volatile("barrier.cluster.arrive.relaxed.aligned;" ::: "memory");
    DBG_T(2);

    {
        const int m = warp & 3, kh = warp >> 2;
        float ca[4] = {0.f, 0.f, 0.f, 0.f}, cb[4] = {0.f, 0.f, 0.f, 0.f};
        const int lrow = (lane & 7) + ((lane >> 4) & 1) * 8;
        const int lchunk = m * 2 + ((lane >> 3) & 1);
        const uint32_t baddr = sb + SM_R2 + (lane & 7) * (PITCH * 2) + (lane >> 3) * 16;
#pragma unroll
        for (int j = 0; j < 5; j++) {
            const int nk = j < 4 ? 4 : 2;
            const int ks0 = j * 8 + kh * nk;
            uint32_t bfr[2][4], afr[4][4];
#pragma unroll
            for (int s = 0; s < nk; s += 2) ldsm_x4(bfr[s / 2][0], bfr[s / 2][1], bfr[s / 2][2], bfr[s / 2][3], baddr + (ks0 + s) * 32);
            mbar_wait(BAR(BAR_FULL + j), 0);
#pragma unroll
            for (int s = 0; s < nk; s++) {
                const int row = (ks0 + s) * 16 + lrow;
                ldsm_x4_t(afr[s][0], afr[s][1], afr[s][2], afr[s][3], sb + row * 128 + ((lchunk ^ (row & 7)) << 4));
            }
#pragma unroll
            for (int s = 0; s < nk; s += 2) {
                mma16816(ca, afr[s][0], afr[s][1], afr[s][2], afr[s][3], bfr[s / 2][0], bfr[s / 2][1]);
                mma16816(cb, afr[s + 1][0], afr[s + 1][1], afr[s + 1][2], afr[s + 1][3], bfr[s / 2][2], bfr[s / 2][3]);
            }
            if (j < 4) {
                cons_sync();
                if (warp < 4 && lane == 0) mbar_arrive(BAR(BAR_EMPTY + j));
            }
        }
        DBG_T(19);
        float* red = (float*)(smem + SM_R1);
        red[(kh * 8 + 2 * t) * 64 + m * 16 + g] = ca[0] + cb[0];
        red[(kh * 8 + 2 * t + 1) * 64 + m * 16 + g] = ca[1] + cb[1];
        red[(kh * 8 + 2 * t) * 64 + m * 16 + g + 8] = ca[2] + cb[2];
        red[(kh * 8 + 2 * t + 1) * 64 + m * 16 + g + 8] = ca[3] + cb[3];
        cons_sync();
        if (warp < 4 && lane == 0) mbar_arrive(BAR(BAR_EMPTY + 4));
        asm volatile("barrier.cluster.wait.acquire.aligned;" ::: "memory");
        if (tid < 64) {
            const int b = tid >> 3, oct = tid & 7;
            const float* p0 = red + b * 64 + oct * 8;
            const float4 u0 = *(const float4*)p0, u1 = *(const float4*)(p0 + 4);
            const float4 v0 = *(const float4*)(p0 + 512), v1 = *(const float4*)(p0 + 516);
            const uint4 w = make_uint4(bf16_pack(u0.x + v0.x, u0.y + v0.y), bf16_pack(u0.z + v0.z, u0.w + v0.w),
                                       bf16_pack(u1.x + v1.x, u1.y + v1.y), bf16_pack(u1.z + v1.z, u1.w + v1.w));
            st_async4(mapa(sb + SM_QS + (r * 64 + oct * 8) * 2, b), w, mapa(BAR(BAR_Q), b));
        }
        mbar_wait_cl(BAR(BAR_Q));
        cons_sync();
    }
    DBG_T(3);

    float4 apart = make_float4(0.f, 0.f, 0.f, 0.f);

#pragma unroll 1
    for (int u = 0; u < 2; u++) {
        {
            uint32_t bq[16];
            {
                const int pi = (g >> 1) & 1, h = g & 1;
#pragma unroll
                for (int j = 0; j < 4; j++) {
                    uint4 v = lds128(sb + SM_QS + (u * 2 + h) * 256 + (4 * (j ^ pi) + t) * 16);
                    if (g >= 4) v = make_uint4(0, 0, 0, 0);
                    bq[4 * j] = v.x; bq[4 * j + 1] = v.y; bq[4 * j + 2] = v.z; bq[4 * j + 3] = v.w;
                }
            }
            const int pig = g & 1;
            const int first = (u ? IT_KB : IT_KA) + (warp >> 2);
            int slot = first % NS; uint32_t ph = (first / NS) & 1;
            const uint32_t rowoff = ((warp & 3) * 16 + g) * 256;
            unsigned short* sc = (unsigned short*)(smem + SM_R1);
            float mx0 = -INFINITY, mx1 = -INFINITY;
            for (int kt = warp >> 2; kt < 32; kt += 2) {
                mbar_wait(BAR(BAR_FULL + slot), ph);
                const uint32_t base = sb + slot * SLOT + rowoff;
                uint4 X[4], Y[4];
#pragma unroll
                for (int j = 0; j < 4; j++) {
                    const uint32_t a = base + (4 * (j ^ pig) + t) * 16;
                    X[j] = lds128(a); Y[j] = lds128(a + 2048);
                }
                float ca[4] = {0.f, 0.f, 0.f, 0.f}, cb[4] = {0.f, 0.f, 0.f, 0.f};
#pragma unroll
                for (int j = 0; j < 4; j++) {
                    mma16816(ca, X[j].x, Y[j].x, X[j].y, Y[j].y, bq[4 * j], bq[4 * j + 1]);
                    mma16816(cb, X[j].z, Y[j].z, X[j].w, Y[j].w, bq[4 * j + 2], bq[4 * j + 3]);
                }
                __syncwarp();
                if (lane == 0) mbar_arrive(BAR(BAR_EMPTY + slot));
                if (t == pig) {
                    const int key = kt * 64 + (warp & 3) * 16 + g;
                    const float scale = 0.08838834764831845f;
                    const uint32_t s0 = bf16_pack(bf16r(ca[0] + cb[0]) * scale, bf16r(ca[2] + cb[2]) * scale);
                    const uint32_t s1 = bf16_pack(bf16r(ca[1] + cb[1]) * scale, bf16r(ca[3] + cb[3]) * scale);
                    sc[key] = (unsigned short)s0; sc[key + 8] = (unsigned short)(s0 >> 16);
                    sc[2048 + key] = (unsigned short)s1; sc[2048 + key + 8] = (unsigned short)(s1 >> 16);
                    mx0 = fmaxf(mx0, fmaxf(bf_lo(s0), bf_hi(s0)));
                    mx1 = fmaxf(mx1, fmaxf(bf_lo(s1), bf_hi(s1)));
                }
                slot += 2; if (slot >= NS) { slot -= NS; ph ^= 1; }
            }
            mx0 = warp_max(mx0); mx1 = warp_max(mx1);
            if (lane == 0) { float* stat = (float*)(smem + SM_STAT); stat[warp] = mx0; stat[8 + warp] = mx1; }
        }
        cons_sync();
        if (u == 0) DBG_T(4); else DBG_T(7);

        {
            const int h = tid >> 7, idx = tid & 127;
            const uint32_t a = sb + SM_R1 + h * 4096 + idx * 32;
            const uint4 u0 = lds128(a), u1 = lds128(a + 16);
            float e[16];
            e[0] = bf_lo(u0.x); e[1] = bf_hi(u0.x); e[2] = bf_lo(u0.y); e[3] = bf_hi(u0.y);
            e[4] = bf_lo(u0.z); e[5] = bf_hi(u0.z); e[6] = bf_lo(u0.w); e[7] = bf_hi(u0.w);
            e[8] = bf_lo(u1.x); e[9] = bf_hi(u1.x); e[10] = bf_lo(u1.y); e[11] = bf_hi(u1.y);
            e[12] = bf_lo(u1.z); e[13] = bf_hi(u1.z); e[14] = bf_lo(u1.w); e[15] = bf_hi(u1.w);
            float* stat = (float*)(smem + SM_STAT);
            const float4 ma = *(const float4*)(stat + h * 8), mb = *(const float4*)(stat + h * 8 + 4);
            const float mx = fmaxf(fmaxf(fmaxf(ma.x, ma.y), fmaxf(ma.z, ma.w)), fmaxf(fmaxf(mb.x, mb.y), fmaxf(mb.z, mb.w)));
            float sum = 0.f;
#pragma unroll
            for (int i = 0; i < 16; i++) {
                asm("ex2.approx.ftz.f32 %0, %1;" : "=f"(e[i]) : "f"((e[i] - mx) * 1.4426950408889634f));
                sum += e[i];
            }
            sum = warp_sum(sum);
            if (lane == 0) stat[16 + warp] = sum;
            cons_sync();
            sum = (stat[16 + h * 4] + stat[16 + h * 4 + 1]) + (stat[16 + h * 4 + 2] + stat[16 + h * 4 + 3]);
            const float inv = __fdiv_rn(1.0f, sum);
            uint32_t w[8];
#pragma unroll
            for (int i = 0; i < 8; i++) w[i] = bf16_pack(e[2 * i] * inv, e[2 * i + 1] * inv);
            *(uint4*)(smem + SM_R1 + h * 4096 + idx * 32) = make_uint4(w[0], w[1], w[2], w[3]);
            *(uint4*)(smem + SM_R1 + h * 4096 + idx * 32 + 16) = make_uint4(w[4], w[5], w[6], w[7]);
            cons_sync();
        }
        if (u == 0) DBG_T(5);

        {
            float acc[2][4][4];
#pragma unroll
            for (int a = 0; a < 2; a++)
#pragma unroll
                for (int b = 0; b < 4; b++)
#pragma unroll
                    for (int d = 0; d < 4; d++) acc[a][b][d] = 0.f;
            const int first = (u ? IT_VB : IT_VA) + (warp >> 2);
            const bool bvalid = (g >> 1) == t;
            const uint32_t paddr = sb + SM_R1 + (g & 1) * 4096 + ((warp & 3) * 16 + 4 * t) * 2;
            const uint32_t rowoff = ((warp & 3) * 16 + 4 * t) * 256 + (g ^ (2 * t)) * 16;
            for (int vt = warp >> 2; vt < 32; vt += 2) {
                const int item = first - (warp >> 2) + vt;
                const int slot = item_slot(item);
                const uint2 pbv = lds64(paddr + vt * 128);
                const uint32_t b0 = bvalid ? pbv.x : 0u, b1 = bvalid ? pbv.y : 0u;
                mbar_wait(BAR(BAR_FULL + slot), item_par(item));
                if (u == 1 && vt == TRIG_TILE && tid == 0) mbar_arrive(BAR(BAR_TRIG));
                const uint32_t base = sb + slot * SLOT + rowoff;
                uint4 X[2][4];
#pragma unroll
                for (int hf = 0; hf < 2; hf++)
#pragma unroll
                    for (int i = 0; i < 4; i++) X[hf][i] = lds128(base + i * 256 + hf * 128);
#pragma unroll
                for (int hf = 0; hf < 2; hf++) {
                    const uint32_t x0[4] = {X[hf][0].x, X[hf][0].y, X[hf][0].z, X[hf][0].w};
                    const uint32_t x1[4] = {X[hf][1].x, X[hf][1].y, X[hf][1].z, X[hf][1].w};
                    const uint32_t x2[4] = {X[hf][2].x, X[hf][2].y, X[hf][2].z, X[hf][2].w};
                    const uint32_t x3[4] = {X[hf][3].x, X[hf][3].y, X[hf][3].z, X[hf][3].w};
#pragma unroll
                    for (int m = 0; m < 4; m++) {
                        mma16816(acc[hf][m], __byte_perm(x0[m], x1[m], 0x5410), __byte_perm(x0[m], x1[m], 0x7632),
                                 __byte_perm(x2[m], x3[m], 0x5410), __byte_perm(x2[m], x3[m], 0x7632), b0, b1);
                    }
                }
                __syncwarp();
                if (lane == 0) mbar_arrive(BAR(BAR_EMPTY + slot));
            }
            if (u == 0) DBG_T(6); else DBG_T(8);
            float k1[4][4];
            {
                const bool up = (t & 2) != 0;
#pragma unroll
                for (int m = 0; m < 4; m++)
#pragma unroll
                    for (int d = 0; d < 4; d++) {
                        const float keep = up ? acc[1][m][d] : acc[0][m][d];
                        const float send = up ? acc[0][m][d] : acc[1][m][d];
                        k1[m][d] = keep + __shfl_xor_sync(0xffffffffu, send, 18);
                    }
            }
            float k2[2][4];
            {
                const bool up = (t & 1) != 0;
#pragma unroll
                for (int m = 0; m < 2; m++)
#pragma unroll
                    for (int d = 0; d < 4; d++) {
                        const float keep = up ? k1[2 + m][d] : k1[m][d];
                        const float send = up ? k1[m][d] : k1[2 + m][d];
                        k2[m][d] = keep + __shfl_xor_sync(0xffffffffu, send, 9);
                    }
            }
            float* red = (float*)(smem + SM_R2);
            {
                const int d0 = ((g ^ (2 * t)) + 8 * (t >> 1)) * 8 + (t & 1) * 4;
                *(float4*)(red + warp * 256 + d0) = make_float4(k2[0][0], k2[0][2], k2[1][0], k2[1][2]);
                *(float4*)(red + warp * 256 + 128 + d0) = make_float4(k2[0][1], k2[0][3], k2[1][1], k2[1][3]);
            }
            cons_sync();
            float s = 0.f;
#pragma unroll
            for (int w = 0; w < 8; w++) s += red[w * 256 + tid];
            const uint32_t obuf = sb + SM_R3 + u * (NB * OPITCH * 2);
            const uint32_t obar = BAR(u ? BAR_OB : BAR_OA);
            ((unsigned short*)(smem + SM_OL))[tid] = (unsigned short)bf16_bits(s);
            cons_sync();
            const uint4 ov = lds128(sb + SM_OL + lane * 16);
            st_async4(mapa(obuf + r * (OPITCH * 2) + lane * 16, warp), ov, mapa(obar, warp));
            if (u == 0) {
#pragma unroll
                for (int j = 0; j < 3; j++) mbar_wait(BAR(BAR_FULL + (IT_WOA + j) % NS), ((IT_WOA + j) / NS) & 1);
            } else {
#pragma unroll
                for (int j = 0; j < 3; j++) mbar_wait(BAR(BAR_TW + j), 0);
            }
            const uint32_t wbase = u ? sb + TAIL : sb + (IT_WOA % NS) * SLOT;
            const uint32_t wstride = u ? CHUNK : SLOT;
            uint32_t af[4][3][4];
            gemv_load<4>(af, [&](int k) { return wbase + k * wstride; }, tid);
            mbar_wait_cl(obar);
            if (u == 1) DBG_T(9);
            const float4 p = gemv_mma<4>(af, obuf, OPITCH, (float*)(smem + SM_R2), tid);
            apart.x += p.x; apart.y += p.y; apart.z += p.z; apart.w += p.w;
            if (u == 0) {
                if (warp < 4 && lane == 0) {
#pragma unroll
                    for (int j = 0; j < 3; j++) mbar_arrive(BAR(BAR_EMPTY + (IT_WOA + j) % NS));
                }
                cons_sync();
            }
        }
    }

    uint32_t hw0 = 0, hw1 = 0;
    uint32_t af[9][3][4];
    if (tid < 144) {
        mbar_wait(BAR(BAR_RSTOK), 0);
        st_pub4(&g_scr.ap[r][cl][tid * 4], make_uint4(f2pub(apart.x), f2pub(apart.y), f2pub(apart.z), f2pub(apart.w)));
        DBG_T(10);
    }
    if (tid < 144) {
        { const long long c0 = clock64(); while (clock64() - c0 < POLL_DELAY) { } }
        uint4 v[NCL];
        const uint32_t* ap0 = &g_scr.ap[r][0][tid * 4];
        uint32_t spins = 0;
        while (true) {
#pragma unroll
            for (int c = 0; c < NCL; c++) v[c] = ld_poll4(ap0 + c * 576);
            uint32_t bad = 0;
#pragma unroll
            for (int c = 0; c < NCL; c++)
                bad |= (uint32_t)(v[c].x == SENT) | (uint32_t)(v[c].y == SENT) | (uint32_t)(v[c].z == SENT) | (uint32_t)(v[c].w == SENT);
            if (bad == 0) break;
            if (++spins > (1u << 22)) __trap();
        }
        float s0 = 0.f, s1 = 0.f, s2 = 0.f, s3 = 0.f;
#pragma unroll
        for (int c = 0; c < NCL; c++) {
            s0 += __uint_as_float(v[c].x); s1 += __uint_as_float(v[c].y);
            s2 += __uint_as_float(v[c].z); s3 += __uint_as_float(v[c].w);
        }
        if (tid == 0) mbar_arrive(BAR(BAR_WOFREE));
        DBG_T(25);
        const float h0 = bf16r(bf_lo(xres.x) + bf16r(s0)), h1 = bf16r(bf_hi(xres.x) + bf16r(s1));
        const float h2 = bf16r(bf_lo(xres.y) + bf16r(s2)), h3 = bf16r(bf_hi(xres.y) + bf16r(s3));
        hw0 = bf16_pack(h0, h1); hw1 = bf16_pack(h2, h3);
        if (qb == cl) *(float4*)(smem + SM_HS + qq * 16) = make_float4(h0, h1, h2, h3);
    }
    __syncwarp();
    if (warp < 5) send_slice(hw0, hw1, sb + SM_R1, BAR(BAR_H), r, tid);
    DBG_T(11);
    {
        const int c0 = (9 * (warp & 3)) / 6;
        mbar_wait(BAR(BAR_TW + 3 + c0), 0);
        mbar_wait(BAR(BAR_TW + 3 + c0 + 1), 0);
    }
    DBG_T(27);
    gemv_load<9>(af, [&](int k) { return sb + TAIL_W1 + k * CHUNK; }, tid);
    mbar_wait_cl(BAR(BAR_H));
    DBG_T(20);
    {
        uint32_t* row = (uint32_t*)(smem + SM_R1) + warp * (PITCH / 2);
        uint32_t w[9];
#pragma unroll
        for (int j = 0; j < 9; j++) w[j] = row[j * 32 + lane];
        layernorm_row<true>(w);
#pragma unroll
        for (int j = 0; j < 9; j++) row[j * 32 + lane] = w[j];
    }
    DBG_T(21);
    cons_sync();
    DBG_T(12);

    float4 p = gemv_mma<9>(af, sb + SM_R1, PITCH, (float*)(smem + SM_R2), tid);
    {
        float a = bf16r(p.x), b = bf16r(p.y), c = bf16r(p.z), d = bf16r(p.w);
        a = (a != a) ? a : fmaxf(a, 0.f); b = (b != b) ? b : fmaxf(b, 0.f);
        c = (c != c) ? c : fmaxf(c, 0.f); d = (d != d) ? d : fmaxf(d, 0.f);
        DBG_T(22);
        __syncwarp();
        if (warp < 5) send_slice(bf16_pack(a, b), bf16_pack(c, d), sb + SM_R3, BAR(BAR_H1), r, tid);
        DBG_T(23);
    }
    {
        auto addr = [&](int k) { return k < 4 ? sb + k * SLOT : sb + TAIL + (k - 4) * CHUNK; };
        auto wait = [&](int k) { mbar_wait(BAR(BAR_TW + 9 + k), 0); };
        auto awaitf = [&]() { mbar_wait_cl(BAR(BAR_H1)); DBG_T(13); };
        if (tid < 128) gemv_w2_t<3>(af, addr, wait, awaitf, sb + SM_R3, PITCH, (float*)(smem + SM_R2), tid);
        else gemv_w2_t<2>(af, addr, wait, awaitf, sb + SM_R3, PITCH, (float*)(smem + SM_R2), tid);
    }
    cons_sync();
    if (tid < 144) {
        const float* red = (const float*)(smem + SM_R2);
        const float4 p0 = *(const float4*)(red + tid * 4), p1 = *(const float4*)(red + 576 + tid * 4);
        const float4 p2 = *(const float4*)(red + 1152 + tid * 4), p3 = *(const float4*)(red + 1728 + tid * 4);
        p.x = (p0.x + p1.x) + (p2.x + p3.x); p.y = (p0.y + p1.y) + (p2.y + p3.y);
        p.z = (p0.z + p1.z) + (p2.z + p3.z); p.w = (p0.w + p1.w) + (p2.w + p3.w);
    }
    {
        if (tid < 144) {
            st_pub4(&g_scr.fp[r][cl][tid * 4], make_uint4(f2pub(p.x), f2pub(p.y), f2pub(p.z), f2pub(p.w)));
            DBG_T(14);
            { const long long c0 = clock64(); while (clock64() - c0 < POLL_DELAY) { } }
            const int quad = tid >> 3, c = tid & 7;
            uint4 w;
            uint32_t spins = 0;
            while (true) {
                w = ld_poll4(&g_scr.fp[r][c][cl * 72 + quad * 4]);
                if (vec_valid(w)) break;
                if (++spins > (1u << 22)) __trap();
            }
            apart = make_float4(__uint_as_float(w.x), __uint_as_float(w.y), __uint_as_float(w.z), __uint_as_float(w.w));
        } else {
            apart = make_float4(0.f, 0.f, 0.f, 0.f);
        }
        if (warp < 5) {
            __syncwarp();
#pragma unroll
            for (int o = 1; o < 8; o <<= 1) {
                apart.x += __shfl_xor_sync(0xffffffffu, apart.x, o); apart.y += __shfl_xor_sync(0xffffffffu, apart.y, o);
                apart.z += __shfl_xor_sync(0xffffffffu, apart.z, o); apart.w += __shfl_xor_sync(0xffffffffu, apart.w, o);
            }
            if (tid < 144 && (tid & 7) == 0) {
                const int quad = tid >> 3;
                const float4 h = *(const float4*)(smem + SM_HS + quad * 16);
                uint2 o;
                o.x = bf16_pack(h.x + bf16r(apart.x), h.y + bf16r(apart.y));
                o.y = bf16_pack(h.z + bf16r(apart.z), h.w + bf16r(apart.w));
                *(uint2*)(prm.out + cl * DM + r * 72 + quad * 4) = o;
            }
            if (blockIdx.x == 0 && tid == 0) g_cnt = 0;
            DBG_T(15);
        }
    }
}

typedef CUresult (*EncodeTiledFn)(CUtensorMap*, CUtensorMapDataType, cuuint32_t, void*, const cuuint64_t*, const cuuint64_t*,
                                  const cuuint32_t*, const cuuint32_t*, CUtensorMapInterleave, CUtensorMapSwizzle,
                                  CUtensorMapL2promotion, CUtensorMapFloatOOBfill);

void make_map(EncodeTiledFn fn, CUtensorMap* m, const void* ptr, uint64_t cols, uint64_t rows, uint32_t bc, uint32_t br,
              CUtensorMapSwizzle sw) {
    cuuint64_t dims[2] = {cols, rows};
    cuuint64_t strides[1] = {cols * 2};
    cuuint32_t box[2] = {bc, br};
    cuuint32_t es[2] = {1, 1};
    fn(m, CU_TENSOR_MAP_DATA_TYPE_BFLOAT16, 2, const_cast<void*>(ptr), dims, strides, box, es, CU_TENSOR_MAP_INTERLEAVE_NONE, sw,
       CU_TENSOR_MAP_L2_PROMOTION_L2_256B, CU_TENSOR_MAP_FLOAT_OOB_FILL_NONE);
}

}

extern "C" void kernel_launch(void* const* d_in, const int* in_sizes, int n_in, void* d_out, int out_size) {
    (void)in_sizes; (void)n_in; (void)out_size;
    static EncodeTiledFn enc = nullptr;
    if (!enc) {
        void* fn = nullptr;
        cudaDriverEntryPointQueryResult qr;
        cudaGetDriverEntryPoint("cuTensorMapEncodeTiled", &fn, cudaEnableDefault, &qr);
        enc = (EncodeTiledFn)fn;
        cudaFuncSetAttribute(fused_decode_kernel, cudaFuncAttributeMaxDynamicSharedMemorySize, SM_TOTAL);
    }
    CUtensorMap mq, mo, m1, m2;
    make_map(enc, &mq, d_in[3], 4096, DM, 64, 128, CU_TENSOR_MAP_SWIZZLE_128B);
    make_map(enc, &mo, d_in[4], DM, 4096, 72, 32, CU_TENSOR_MAP_SWIZZLE_NONE);
    make_map(enc, &m1, d_in[6], DFF, DM, 72, 96, CU_TENSOR_MAP_SWIZZLE_NONE);
    make_map(enc, &m2, d_in[7], DM, DFF, 72, 96, CU_TENSOR_MAP_SWIZZLE_NONE);
    Params p;
    p.x = (const __nv_bfloat16*)d_in[0];
    p.k = (const __nv_bfloat16*)d_in[1];
    p.v = (const __nv_bfloat16*)d_in[2];
    p.out = (__nv_bfloat16*)d_out;
    fused_decode_kernel<<<NCTA, 320, SM_TOTAL, cudaStreamPerThread>>>(mq, mo, m1, m2, p);
}
```
